```python
import torch

def _softmax(x, axis=-1):
    return torch.softmax(x, dim=axis)
def _gelu(x):
    return torch.nn.functional.gelu(x, approximate="tanh")
def _silu(x):
    return torch.nn.functional.silu(x)
def _sigmoid(x):
    return torch.sigmoid(x)
def _layernorm(x, axis=-1, eps=1e-5):
    m = x.mean(dim=axis, keepdim=True)
    v = x.var(dim=axis, keepdim=True, unbiased=False)
    return (x - m) / torch.sqrt(v + eps)
def _scatter_add(tgt, idx, src, axis=0):
    return tgt.clone().index_add_(axis, idx, src)
def _segment_sum(src, seg, n):
    out = torch.zeros((n,) + src.shape[1:], dtype=src.dtype)
    return out.index_add_(0, seg, src)
def _pad(x, pw):
    flat = tuple(v for pair in reversed(pw) for v in pair)
    return torch.nn.functional.pad(x, flat)

kernel_name = 'recurrent_scan__ssm_conv_h3__dense_activation_mish__prompt'

def setup_inputs():

    _w = (lambda a: (lambda t: t.to(torch.bfloat16) if t.is_floating_point() else t)(torch.as_tensor(a)))
    def _A_setup():
        B, S, D = 1, 2048, 1024
        ks = 4
        return {
            "q": _w((lambda *s: torch.randn(*s, dtype=torch.bfloat16) * 0.05)(B, S, D)),
            "k": _w((lambda *s: torch.randn(*s, dtype=torch.bfloat16) * 0.8)(B, S, D)),
            "v": _w((lambda *s: torch.randn(*s, dtype=torch.bfloat16) * 0.8)(B, S, D)),
            "shift_k": _w((lambda *s: torch.randn(*s, dtype=torch.bfloat16) * 0.8)(D, ks) * 0.5),
            "ssm_k": _w((lambda *s: torch.randn(*s, dtype=torch.bfloat16) * 0.8)(D, S) * (1.0 / S ** 0.5)),
            "ssm_D": _w((lambda *s: torch.randn(*s, dtype=torch.bfloat16) * 0.8)(D)),
        }
    _A_in = _A_setup()

    def _B_setup():
        B, S, D, F = 1, 2048, 1024, 3584
        return {
            "x": _w((lambda *s: torch.randn(*s, dtype=torch.bfloat16) * 0.05)(B, S, D)),
            "w1": _w((lambda *s: torch.randn(*s, dtype=torch.bfloat16) * 0.8)(D, F) * (D ** -0.5)),
            "b1": _w((lambda *s: torch.randn(*s, dtype=torch.bfloat16) * 0.2)(F)),
            "w2": _w((lambda *s: torch.randn(*s, dtype=torch.bfloat16) * 0.2)(F, D) * (F ** -0.5)),
        }
    _B_in = _B_setup()

    return {
        "A_q": _A_in["q"],
        "A_k": _A_in["k"],
        "A_v": _A_in["v"],
        "A_shift_k": _A_in["shift_k"],
        "A_ssm_k": _A_in["ssm_k"],
        "A_ssm_D": _A_in["ssm_D"],
        "B_x": _B_in["x"],
        "B_w1": _B_in["w1"],
        "B_b1": _B_in["b1"],
        "B_w2": _B_in["w2"],
    }

def reference(A_q, A_k, A_v, A_shift_k, A_ssm_k, A_ssm_D, B_x, B_w1, B_b1, B_w2):
    def _A_ref(q, k, v, shift_k, ssm_k, ssm_D):
        B, S, D = q.shape
        ks = shift_k.shape[-1]
        k_pad = _pad(k, ((0, 0), (ks - 1, 0), (0, 0)))
        k_shift = torch.zeros_like(k)
        for t in range(ks):
            k_shift = k_shift + k_pad[:, t:t + S, :] * shift_k[:, ks - 1 - t][None, None, :]
        kv = k_shift * v
        L = 2 * S
        kv_pad = _pad(kv, ((0, 0), (0, S), (0, 0)))
        kf_pad = _pad(ssm_k, ((0, 0), (0, S)))
        kv_f = (lambda x, axes=(-2,-1): torch.fft.rfft2(x.float(), dim=axes))(kv_pad[:, None, :, :], axes=(1, 2))
        kf_f = (lambda x, axes=(-2,-1): torch.fft.rfft2(x.float(), dim=axes))(kf_pad[:, None, :], axes=(1, 2))
        kf_f = (lambda x, *d: x.permute(*d))(kf_f, 1, 2, 0)
        y_f = kv_f * kf_f[None, :, :, :]
        y = (lambda x, s, axes=(-2,-1): torch.fft.irfft2(x, s=s, dim=axes).to(torch.bfloat16))(y_f, (1, L), axes=(1, 2))[:, 0, :S, :]
        y = y + kv * ssm_D[None, None, :]
        return q * y

    def _B_ref(x, w1, b1, w2):
        h = torch.einsum("bsd,df->bsf", x, w1) + b1
        sp = torch.log1p(torch.exp(-torch.abs(h))) + torch.where(h > 0, h, torch.zeros_like(h))
        act = h * torch.tanh(sp)
        return torch.einsum("bsf,fd->bsd", act, w2)

    x = A_q
    xn = _layernorm(x, axis=-1)
    s = _A_ref(xn, A_k, A_v, A_shift_k, A_ssm_k, A_ssm_D)
    g = _silu(_B_ref(xn, B_w1, B_b1, B_w2))
    return x + s * g
```

```cpp
#include <cuda_runtime.h>
#include <cuda.h>
#include <cuda_bf16.h>
#include <stdint.h>

typedef __nv_bfloat16 bf16;
typedef __nv_bfloat162 bf162;
constexpr int S_ = 2048, D_ = 1024, F_ = 3584;
constexpr int UARR = 2176, UCH = 4 * UARR, CHB = UCH + 4096;
constexpr int STAGE = 49152, NST = 4;
constexpr int XOFF = 2 * CHB;
constexpr int SM_XT = NST * STAGE;
constexpr int SM_ST = SM_XT + 32768;
constexpr int SM_CB = SM_ST + 1024;
constexpr int SM_BARS = SM_CB + 1792;
constexpr int SMEM_BYTES = SM_BARS + 256;
constexpr int TAILOFF = 16384 + 224 * 64 * 2;
constexpr int B1BYTES = 224 * 64 * 2;

__device__ __align__(1024) float2 g_stat[S_];
__device__ __align__(1024) float g_csp[16 * F_];
__device__ __align__(1024) bf16 g_act[S_ * F_];
__device__ __align__(1024) uint8_t g_U[(size_t)D_ * UCH];
__device__ __align__(1024) bf16 g_Y[D_ * S_];
enum { C_CS = 0, C_U = 16, C_ACT = 48, C_Y = 80, C_TK = 88 };
__device__ unsigned g_cnt[(C_TK + 1) * 32];
#define STAMP(i)
#define PSTAMP(i)

#define UITER 32
#define XROW 0
#define XCH 2
__device__ __forceinline__ void mma_n224(float (&d)[112], uint64_t da, uint64_t db, int sd) {
  asm volatile("{\n.reg .pred p;\nsetp.ne.b32 p, %114, 0;\n"
    "wgmma.mma_async.sync.aligned.m64n224k16.f32.bf16.bf16 {%0,%1,%2,%3,%4,%5,%6,%7,%8,%9,%10,%11,%12,%13,%14,%15,%16,%17,%18,%19,%20,%21,%22,%23,%24,%25,%26,%27,%28,%29,%30,%31,%32,%33,%34,%35,%36,%37,%38,%39,%40,%41,%42,%43,%44,%45,%46,%47,%48,%49,%50,%51,%52,%53,%54,%55,%56,%57,%58,%59,%60,%61,%62,%63,%64,%65,%66,%67,%68,%69,%70,%71,%72,%73,%74,%75,%76,%77,%78,%79,%80,%81,%82,%83,%84,%85,%86,%87,%88,%89,%90,%91,%92,%93,%94,%95,%96,%97,%98,%99,%100,%101,%102,%103,%104,%105,%106,%107,%108,%109,%110,%111}, %112, %113, p, 1, 1, 0, 1;\n}\n"
    : "+f"(d[0]),"+f"(d[1]),"+f"(d[2]),"+f"(d[3]),"+f"(d[4]),"+f"(d[5]),"+f"(d[6]),"+f"(d[7]),"+f"(d[8]),"+f"(d[9]),"+f"(d[10]),"+f"(d[11]),"+f"(d[12]),"+f"(d[13]),"+f"(d[14]),"+f"(d[15]),"+f"(d[16]),"+f"(d[17]),"+f"(d[18]),"+f"(d[19]),"+f"(d[20]),"+f"(d[21]),"+f"(d[22]),"+f"(d[23]),"+f"(d[24]),"+f"(d[25]),"+f"(d[26]),"+f"(d[27]),"+f"(d[28]),"+f"(d[29]),"+f"(d[30]),"+f"(d[31]),"+f"(d[32]),"+f"(d[33]),"+f"(d[34]),"+f"(d[35]),"+f"(d[36]),"+f"(d[37]),"+f"(d[38]),"+f"(d[39]),"+f"(d[40]),"+f"(d[41]),"+f"(d[42]),"+f"(d[43]),"+f"(d[44]),"+f"(d[45]),"+f"(d[46]),"+f"(d[47]),"+f"(d[48]),"+f"(d[49]),"+f"(d[50]),"+f"(d[51]),"+f"(d[52]),"+f"(d[53]),"+f"(d[54]),"+f"(d[55]),"+f"(d[56]),"+f"(d[57]),"+f"(d[58]),"+f"(d[59]),"+f"(d[60]),"+f"(d[61]),"+f"(d[62]),"+f"(d[63]),"+f"(d[64]),"+f"(d[65]),"+f"(d[66]),"+f"(d[67]),"+f"(d[68]),"+f"(d[69]),"+f"(d[70]),"+f"(d[71]),"+f"(d[72]),"+f"(d[73]),"+f"(d[74]),"+f"(d[75]),"+f"(d[76]),"+f"(d[77]),"+f"(d[78]),"+f"(d[79]),"+f"(d[80]),"+f"(d[81]),"+f"(d[82]),"+f"(d[83]),"+f"(d[84]),"+f"(d[85]),"+f"(d[86]),"+f"(d[87]),"+f"(d[88]),"+f"(d[89]),"+f"(d[90]),"+f"(d[91]),"+f"(d[92]),"+f"(d[93]),"+f"(d[94]),"+f"(d[95]),"+f"(d[96]),"+f"(d[97]),"+f"(d[98]),"+f"(d[99]),"+f"(d[100]),"+f"(d[101]),"+f"(d[102]),"+f"(d[103]),"+f"(d[104]),"+f"(d[105]),"+f"(d[106]),"+f"(d[107]),"+f"(d[108]),"+f"(d[109]),"+f"(d[110]),"+f"(d[111])
    : "l"(da), "l"(db), "r"(sd));
}
__device__ __forceinline__ void mma_n256(float (&d)[128], uint64_t da, uint64_t db, int sd) {
  asm volatile("{\n.reg .pred p;\nsetp.ne.b32 p, %130, 0;\n"
    "wgmma.mma_async.sync.aligned.m64n256k16.f32.bf16.bf16 {%0,%1,%2,%3,%4,%5,%6,%7,%8,%9,%10,%11,%12,%13,%14,%15,%16,%17,%18,%19,%20,%21,%22,%23,%24,%25,%26,%27,%28,%29,%30,%31,%32,%33,%34,%35,%36,%37,%38,%39,%40,%41,%42,%43,%44,%45,%46,%47,%48,%49,%50,%51,%52,%53,%54,%55,%56,%57,%58,%59,%60,%61,%62,%63,%64,%65,%66,%67,%68,%69,%70,%71,%72,%73,%74,%75,%76,%77,%78,%79,%80,%81,%82,%83,%84,%85,%86,%87,%88,%89,%90,%91,%92,%93,%94,%95,%96,%97,%98,%99,%100,%101,%102,%103,%104,%105,%106,%107,%108,%109,%110,%111,%112,%113,%114,%115,%116,%117,%118,%119,%120,%121,%122,%123,%124,%125,%126,%127}, %128, %129, p, 1, 1, 0, 1;\n}\n"
    : "+f"(d[0]),"+f"(d[1]),"+f"(d[2]),"+f"(d[3]),"+f"(d[4]),"+f"(d[5]),"+f"(d[6]),"+f"(d[7]),"+f"(d[8]),"+f"(d[9]),"+f"(d[10]),"+f"(d[11]),"+f"(d[12]),"+f"(d[13]),"+f"(d[14]),"+f"(d[15]),"+f"(d[16]),"+f"(d[17]),"+f"(d[18]),"+f"(d[19]),"+f"(d[20]),"+f"(d[21]),"+f"(d[22]),"+f"(d[23]),"+f"(d[24]),"+f"(d[25]),"+f"(d[26]),"+f"(d[27]),"+f"(d[28]),"+f"(d[29]),"+f"(d[30]),"+f"(d[31]),"+f"(d[32]),"+f"(d[33]),"+f"(d[34]),"+f"(d[35]),"+f"(d[36]),"+f"(d[37]),"+f"(d[38]),"+f"(d[39]),"+f"(d[40]),"+f"(d[41]),"+f"(d[42]),"+f"(d[43]),"+f"(d[44]),"+f"(d[45]),"+f"(d[46]),"+f"(d[47]),"+f"(d[48]),"+f"(d[49]),"+f"(d[50]),"+f"(d[51]),"+f"(d[52]),"+f"(d[53]),"+f"(d[54]),"+f"(d[55]),"+f"(d[56]),"+f"(d[57]),"+f"(d[58]),"+f"(d[59]),"+f"(d[60]),"+f"(d[61]),"+f"(d[62]),"+f"(d[63]),"+f"(d[64]),"+f"(d[65]),"+f"(d[66]),"+f"(d[67]),"+f"(d[68]),"+f"(d[69]),"+f"(d[70]),"+f"(d[71]),"+f"(d[72]),"+f"(d[73]),"+f"(d[74]),"+f"(d[75]),"+f"(d[76]),"+f"(d[77]),"+f"(d[78]),"+f"(d[79]),"+f"(d[80]),"+f"(d[81]),"+f"(d[82]),"+f"(d[83]),"+f"(d[84]),"+f"(d[85]),"+f"(d[86]),"+f"(d[87]),"+f"(d[88]),"+f"(d[89]),"+f"(d[90]),"+f"(d[91]),"+f"(d[92]),"+f"(d[93]),"+f"(d[94]),"+f"(d[95]),"+f"(d[96]),"+f"(d[97]),"+f"(d[98]),"+f"(d[99]),"+f"(d[100]),"+f"(d[101]),"+f"(d[102]),"+f"(d[103]),"+f"(d[104]),"+f"(d[105]),"+f"(d[106]),"+f"(d[107]),"+f"(d[108]),"+f"(d[109]),"+f"(d[110]),"+f"(d[111]),"+f"(d[112]),"+f"(d[113]),"+f"(d[114]),"+f"(d[115]),"+f"(d[116]),"+f"(d[117]),"+f"(d[118]),"+f"(d[119]),"+f"(d[120]),"+f"(d[121]),"+f"(d[122]),"+f"(d[123]),"+f"(d[124]),"+f"(d[125]),"+f"(d[126]),"+f"(d[127])
    : "l"(da), "l"(db), "r"(sd));
}
__device__ __forceinline__ void mma_n128lo(float (&d)[128], uint64_t da, uint64_t db, int sd) {
  asm volatile("{\n.reg .pred p;\nsetp.ne.b32 p, %66, 0;\n"
    "wgmma.mma_async.sync.aligned.m64n128k16.f32.bf16.bf16 {%0,%1,%2,%3,%4,%5,%6,%7,%8,%9,%10,%11,%12,%13,%14,%15,%16,%17,%18,%19,%20,%21,%22,%23,%24,%25,%26,%27,%28,%29,%30,%31,%32,%33,%34,%35,%36,%37,%38,%39,%40,%41,%42,%43,%44,%45,%46,%47,%48,%49,%50,%51,%52,%53,%54,%55,%56,%57,%58,%59,%60,%61,%62,%63}, %64, %65, p, 1, 1, 0, 1;\n}\n"
    : "+f"(d[0]),"+f"(d[1]),"+f"(d[2]),"+f"(d[3]),"+f"(d[4]),"+f"(d[5]),"+f"(d[6]),"+f"(d[7]),"+f"(d[8]),"+f"(d[9]),"+f"(d[10]),"+f"(d[11]),"+f"(d[12]),"+f"(d[13]),"+f"(d[14]),"+f"(d[15]),"+f"(d[16]),"+f"(d[17]),"+f"(d[18]),"+f"(d[19]),"+f"(d[20]),"+f"(d[21]),"+f"(d[22]),"+f"(d[23]),"+f"(d[24]),"+f"(d[25]),"+f"(d[26]),"+f"(d[27]),"+f"(d[28]),"+f"(d[29]),"+f"(d[30]),"+f"(d[31]),"+f"(d[32]),"+f"(d[33]),"+f"(d[34]),"+f"(d[35]),"+f"(d[36]),"+f"(d[37]),"+f"(d[38]),"+f"(d[39]),"+f"(d[40]),"+f"(d[41]),"+f"(d[42]),"+f"(d[43]),"+f"(d[44]),"+f"(d[45]),"+f"(d[46]),"+f"(d[47]),"+f"(d[48]),"+f"(d[49]),"+f"(d[50]),"+f"(d[51]),"+f"(d[52]),"+f"(d[53]),"+f"(d[54]),"+f"(d[55]),"+f"(d[56]),"+f"(d[57]),"+f"(d[58]),"+f"(d[59]),"+f"(d[60]),"+f"(d[61]),"+f"(d[62]),"+f"(d[63])
    : "l"(da), "l"(db), "r"(sd));
}
__device__ __forceinline__ void mma_n128hi(float (&d)[128], uint64_t da, uint64_t db, int sd) {
  asm volatile("{\n.reg .pred p;\nsetp.ne.b32 p, %66, 0;\n"
    "wgmma.mma_async.sync.aligned.m64n128k16.f32.bf16.bf16 {%0,%1,%2,%3,%4,%5,%6,%7,%8,%9,%10,%11,%12,%13,%14,%15,%16,%17,%18,%19,%20,%21,%22,%23,%24,%25,%26,%27,%28,%29,%30,%31,%32,%33,%34,%35,%36,%37,%38,%39,%40,%41,%42,%43,%44,%45,%46,%47,%48,%49,%50,%51,%52,%53,%54,%55,%56,%57,%58,%59,%60,%61,%62,%63}, %64, %65, p, 1, 1, 0, 1;\n}\n"
    : "+f"(d[64]),"+f"(d[65]),"+f"(d[66]),"+f"(d[67]),"+f"(d[68]),"+f"(d[69]),"+f"(d[70]),"+f"(d[71]),"+f"(d[72]),"+f"(d[73]),"+f"(d[74]),"+f"(d[75]),"+f"(d[76]),"+f"(d[77]),"+f"(d[78]),"+f"(d[79]),"+f"(d[80]),"+f"(d[81]),"+f"(d[82]),"+f"(d[83]),"+f"(d[84]),"+f"(d[85]),"+f"(d[86]),"+f"(d[87]),"+f"(d[88]),"+f"(d[89]),"+f"(d[90]),"+f"(d[91]),"+f"(d[92]),"+f"(d[93]),"+f"(d[94]),"+f"(d[95]),"+f"(d[96]),"+f"(d[97]),"+f"(d[98]),"+f"(d[99]),"+f"(d[100]),"+f"(d[101]),"+f"(d[102]),"+f"(d[103]),"+f"(d[104]),"+f"(d[105]),"+f"(d[106]),"+f"(d[107]),"+f"(d[108]),"+f"(d[109]),"+f"(d[110]),"+f"(d[111]),"+f"(d[112]),"+f"(d[113]),"+f"(d[114]),"+f"(d[115]),"+f"(d[116]),"+f"(d[117]),"+f"(d[118]),"+f"(d[119]),"+f"(d[120]),"+f"(d[121]),"+f"(d[122]),"+f"(d[123]),"+f"(d[124]),"+f"(d[125]),"+f"(d[126]),"+f"(d[127])
    : "l"(da), "l"(db), "r"(sd));
}
__device__ __forceinline__ void cmma(float (&d)[16], uint32_t a0, uint32_t a1, uint32_t a2, uint32_t a3, uint64_t db, int sd) {
  asm volatile("{\n.reg .pred p;\nsetp.ne.b32 p, %21, 0;\n"
    "wgmma.mma_async.sync.aligned.m64n32k16.f32.bf16.bf16 {%0,%1,%2,%3,%4,%5,%6,%7,%8,%9,%10,%11,%12,%13,%14,%15}, {%16,%17,%18,%19}, %20, p, 1, 1, 0;\n}\n"
    : "+f"(d[0]),"+f"(d[1]),"+f"(d[2]),"+f"(d[3]),"+f"(d[4]),"+f"(d[5]),"+f"(d[6]),"+f"(d[7]),"+f"(d[8]),"+f"(d[9]),"+f"(d[10]),"+f"(d[11]),"+f"(d[12]),"+f"(d[13]),"+f"(d[14]),"+f"(d[15])
    : "r"(a0), "r"(a1), "r"(a2), "r"(a3), "l"(db), "r"(sd));
}

__device__ __forceinline__ void wg_fence() { asm volatile("wgmma.fence.sync.aligned;" ::: "memory"); }
__device__ __forceinline__ void wg_commit() { asm volatile("wgmma.commit_group.sync.aligned;" ::: "memory"); }
template <int N> __device__ __forceinline__ void wg_wait() { asm volatile("wgmma.wait_group.sync.aligned %0;" ::"n"(N) : "memory"); }
__device__ __forceinline__ uint64_t mkdesc(uint32_t addr, uint32_t lbo, uint32_t sbo, uint32_t swz) {
  return (uint64_t)((addr & 0x3FFFF) >> 4) | ((uint64_t)(lbo >> 4) << 16) | ((uint64_t)(sbo >> 4) << 32) | ((uint64_t)swz << 62);
}
__device__ __forceinline__ uint32_t smem_u32(const void* p) { return (uint32_t)__cvta_generic_to_shared(p); }
__device__ __forceinline__ void mbar_init(uint32_t bar, uint32_t cnt) { asm volatile("mbarrier.init.shared::cta.b64 [%0], %1;" ::"r"(bar), "r"(cnt) : "memory"); }
__device__ __forceinline__ void mbar_expect_tx(uint32_t bar, uint32_t bytes) { asm volatile("mbarrier.arrive.expect_tx.shared::cta.b64 _, [%0], %1;" ::"r"(bar), "r"(bytes) : "memory"); }
__device__ __forceinline__ void mbar_arrive(uint32_t bar) { asm volatile("mbarrier.arrive.shared::cta.b64 _, [%0];" ::"r"(bar) : "memory"); }
__device__ __forceinline__ void mbar_arrive8(uint32_t bar) { asm volatile("mbarrier.arrive.shared::cta.b64 _, [%0], 8;" ::"r"(bar) : "memory"); }
__device__ __forceinline__ uint32_t mapa(uint32_t a, uint32_t cta) { uint32_t r; asm volatile("mapa.shared::cluster.u32 %0, %1, %2;" : "=r"(r) : "r"(a), "r"(cta)); return r; }
__device__ __forceinline__ void mbar_arrive_remote(uint32_t rbar) { asm volatile("mbarrier.arrive.shared::cluster.b64 _, [%0];" ::"r"(rbar) : "memory"); }
__device__ __forceinline__ void mbar_wait(uint32_t bar, uint32_t parity) {
  asm volatile("{\n.reg .pred p;\n.reg .u32 n;\nmov.u32 n, 0;\nLW:\nmbarrier.try_wait.parity.shared::cta.b64 p, [%0], %1;\n@p bra LD;\n"
               "add.u32 n, n, 1;\nsetp.lt.u32 p, n, 4000000;\n@p bra LW;\ntrap;\nLD:\n}\n" ::"r"(bar), "r"(parity) : "memory");
}
__device__ __forceinline__ void mbar_wait_cluster(uint32_t bar, uint32_t parity) {
  asm volatile("{\n.reg .pred p;\n.reg .u32 n;\nmov.u32 n, 0;\nLW:\nmbarrier.try_wait.parity.acquire.cluster.shared::cta.b64 p, [%0], %1;\n@p bra LD;\n"
               "add.u32 n, n, 1;\nsetp.lt.u32 p, n, 4000000;\n@p bra LW;\ntrap;\nLD:\n}\n" ::"r"(bar), "r"(parity) : "memory");
}
__device__ __forceinline__ void tma2d(uint32_t dst, const CUtensorMap* m, uint32_t bar, int c0, int c1) {
  asm volatile("cp.async.bulk.tensor.2d.shared::cluster.global.mbarrier::complete_tx::bytes [%0], [%1, {%3, %4}], [%2];" ::"r"(dst), "l"(m), "r"(bar), "r"(c0), "r"(c1) : "memory");
}
__device__ __forceinline__ void tma3d_mc(uint32_t dst, const CUtensorMap* m, uint32_t bar, int c0, int c1, int c2, uint16_t mask) {
  asm volatile("cp.async.bulk.tensor.3d.shared::cluster.global.mbarrier::complete_tx::bytes.multicast::cluster [%0], [%1, {%3, %4, %5}], [%2], %6;" ::"r"(dst), "l"(m), "r"(bar), "r"(c0), "r"(c1), "r"(c2), "h"(mask) : "memory");
}
__device__ __forceinline__ void tma5d(uint32_t dst, const CUtensorMap* m, uint32_t bar, int c0, int c4) {
  asm volatile("cp.async.bulk.tensor.5d.shared::cluster.global.mbarrier::complete_tx::bytes [%0], [%1, {%3, %5, %5, %5, %4}], [%2];" ::"r"(dst), "l"(m), "r"(bar), "r"(c0), "r"(c4), "r"(0) : "memory");
}
__device__ __forceinline__ void tma2d_store(const CUtensorMap* m, uint32_t src, int c0, int c1) {
  asm volatile("cp.async.bulk.tensor.2d.global.shared::cta.bulk_group [%0, {%2, %3}], [%1];" ::"l"(m), "r"(src), "r"(c0), "r"(c1) : "memory");
}
__device__ __forceinline__ void bulk_g2s(uint32_t dst, const void* src, uint32_t bytes, uint32_t bar) {
  asm volatile("cp.async.bulk.shared::cluster.global.mbarrier::complete_tx::bytes [%0], [%1], %2, [%3];" ::"r"(dst), "l"(src), "r"(bytes), "r"(bar) : "memory");
}
__device__ __forceinline__ void fence_async() { asm volatile("fence.proxy.async.global;" ::: "memory"); }
__device__ __forceinline__ void bar_sync(int id, int n) { asm volatile("bar.sync %0, %1;" ::"r"(id), "r"(n) : "memory"); }
__device__ __forceinline__ void bar_arrive(int id, int n) { asm volatile("bar.arrive %0, %1;" ::"r"(id), "r"(n) : "memory"); }
__device__ __forceinline__ uint32_t lds32(uint32_t a) { uint32_t v; asm volatile("ld.volatile.shared.b32 %0, [%1];" : "=r"(v) : "r"(a)); return v; }
__device__ __forceinline__ void sts128(uint32_t a, float x, float y, float z, float w) { asm volatile("st.shared.v4.f32 [%0], {%1,%2,%3,%4};" ::"r"(a), "f"(x), "f"(y), "f"(z), "f"(w) : "memory"); }
__device__ __forceinline__ float4 lds128(uint32_t a) { float4 v; asm volatile("ld.shared.v4.f32 {%0,%1,%2,%3}, [%4];" : "=f"(v.x), "=f"(v.y), "=f"(v.z), "=f"(v.w) : "r"(a) : "memory"); return v; }
__device__ __forceinline__ void stg128(void* p, uint32_t a, uint32_t b, uint32_t c, uint32_t d) { asm volatile("st.global.v4.b32 [%0], {%1,%2,%3,%4};" ::"l"(p), "r"(a), "r"(b), "r"(c), "r"(d) : "memory"); }
__device__ __forceinline__ void signal(unsigned* c) { asm volatile("red.release.gpu.global.add.u32 [%0], 1;" ::"l"(c) : "memory"); }
__device__ __forceinline__ void wait_cnt(const unsigned* c, unsigned target) {
  unsigned v, n = 0;
  while (true) {
    asm volatile("ld.acquire.gpu.global.u32 %0, [%1];" : "=r"(v) : "l"(c) : "memory");
    if (v >= target) break;
    if (++n > (1u << 21)) asm volatile("trap;");
    __nanosleep(20);
  }
}
__device__ __forceinline__ uint32_t pack2(float lo, float hi) { uint32_t r; asm("cvt.rn.bf16x2.f32 %0, %1, %2;" : "=r"(r) : "f"(hi), "f"(lo)); return r; }
__device__ __forceinline__ float blo(uint32_t v) { return __uint_as_float(v << 16); }
__device__ __forceinline__ float bhi(uint32_t v) { return __uint_as_float(v & 0xffff0000u); }
__device__ __forceinline__ float rbf(float x) { return __bfloat162float(__float2bfloat16_rn(x)); }
__device__ __forceinline__ uint32_t hmul2(uint32_t a, uint32_t b) { uint32_t r; asm("mul.rn.bf16x2 %0, %1, %2;" : "=r"(r) : "r"(a), "r"(b)); return r; }
__device__ __forceinline__ uint32_t hadd2(uint32_t a, uint32_t b) { uint32_t r; asm("add.rn.bf16x2 %0, %1, %2;" : "=r"(r) : "r"(a), "r"(b)); return r; }
__device__ __forceinline__ uint32_t ldg32(const void* p) { uint32_t v; asm volatile("ld.global.nc.b32 %0, [%1];" : "=r"(v) : "l"(p)); return v; }
__device__ __forceinline__ float ex2(float x) { float r; asm("ex2.approx.ftz.f32 %0, %1;" : "=f"(r) : "f"(x)); return r; }
__device__ __forceinline__ float rcp(float x) { float r; asm("rcp.approx.ftz.f32 %0, %1;" : "=f"(r) : "f"(x)); return r; }
__device__ __forceinline__ float mish(float h) {
  float e = ex2(fminf(h * 1.4426950408889634f, 30.f));
  float n = e * (e + 2.f);
  return h * n * rcp(n + 2.f);
}
__device__ __forceinline__ float silu(float z) { return z * rcp(1.f + ex2(z * -1.4426950408889634f)); }

__device__ __forceinline__ uint32_t cpy(uint32_t v, uint32_t z) { uint32_t r; asm volatile("xor.b32 %0, %1, %2;" : "=r"(r) : "r"(v), "r"(z)); return r; }
template <int HG> __device__ __forceinline__ void loadA(uint32_t (&x)[16], uint32_t hb) {
  uint32_t b = hb + (HG >> 1) * 1024 + (HG & 1) * 128;
  x[0] = lds32(b); x[2] = lds32(b + 16);
#pragma unroll
  for (int r = 0; r < 4; r++) { x[4 * r + 1] = lds32(b + (2 * r + 2) * 16); x[4 * r + 3] = lds32(b + (2 * r + 3) * 16); }
}
__device__ __forceinline__ void dupA(uint32_t (&x)[16], uint32_t z) {
#pragma unroll
  for (int r = 0; r < 3; r++) { x[4 * r + 4] = cpy(x[4 * r + 1], z); x[4 * r + 6] = cpy(x[4 * r + 3], z); }
}
template <int HG> __device__ __forceinline__ void mmaG(float (&d)[4][16], uint32_t (&x)[16], uint64_t dbase) {
  wg_fence();
#pragma unroll
  for (int rr = 0; rr < 4; rr++) {
    constexpr int SP = HG >> 1;
    int r = (HG & 1) * 4 + rr;
    uint64_t db = dbase + (uint64_t)(((r & 1) * 2 * UARR + (SP * 16 + (r >> 1)) * 32) >> 4);
    int sd = (HG | rr) != 0;
#pragma unroll
    for (int c = 0; c < 4 - SP; c++) cmma(d[c], x[4 * rr], x[4 * rr + 1], x[4 * rr + 2], x[4 * rr + 3], db + 32 * c, sd);
  }
  wg_commit();
}

struct Params {
  const bf16 *x, *k, *v, *shk, *hk, *Dv, *b1;
  uint32_t zero;
};

template <int NC> __device__ __forceinline__ void act_chunk(uint32_t (&hp)[56], bf16* dst) {
#pragma unroll
  for (int c = 0; c < NC; c++) {
    uint32_t o[4];
#pragma unroll
    for (int i = 0; i < 4; i++) o[i] = pack2(mish(blo(hp[4 * c + i])), mish(bhi(hp[4 * c + i])));
    stg128(dst + c * 8 * F_, o[0], o[1], o[2], o[3]);
  }
#pragma unroll
  for (int i = 0; i < 56 - 4 * NC; i++) hp[i] = hp[i + 4 * NC];
}

enum { NB_ORD0 = 1, NB_ORD1 = 2, NB_WG0 = 3, NB_WG1 = 4, NB_CS = 5, NB_ACT = 6, NB_Y = 7, NB_HLP = 8 };

__global__ void __cluster_dims__(2, 1, 1) __launch_bounds__(384, 1)
fused_kernel(const __grid_constant__ CUtensorMap m_x, const __grid_constant__ CUtensorMap m_w1, const __grid_constant__ CUtensorMap m_act,
             const __grid_constant__ CUtensorMap m_w2, const __grid_constant__ CUtensorMap m_y, const __grid_constant__ CUtensorMap m_out,
             const __grid_constant__ CUtensorMap m_k, const __grid_constant__ CUtensorMap m_v, const Params p) {
  extern __shared__ __align__(1024) uint8_t smem_raw[];
  const uint32_t sb = smem_u32(smem_raw);
  const uint32_t bfull = sb + SM_BARS, bempty = bfull + 32, brdy = bfull + 64, bdat = bfull + 72, bepi = bfull + 88, bxt = bfull + 96, bdep = bfull + 104, bhlp = bfull + 136, bkv = bfull + 144;
  const uint32_t s_cb = sb + SM_CB, s_st = sb + SM_ST, s_xt = sb + SM_XT;
  const int wg = __shfl_sync(0xffffffff, threadIdx.x / 128, 0);
  const int cta = blockIdx.x, cid = cta >> 1, rank = cta & 1;
  if (threadIdx.x == 0) {
    for (int s = 0; s < NST; s++) { mbar_init(bfull + s * 8, 1); mbar_init(bempty + s * 8, 16); }
    mbar_init(brdy, 2); mbar_init(bdat, 1); mbar_init(bdat + 8, 1); mbar_init(bepi, 1); mbar_init(bxt, 1);
    for (int s = 0; s < 4; s++) { mbar_init(bdep + s * 8, 1); mbar_init(bkv + s * 8, 1); }
    mbar_init(bhlp, 1);
    if (sb & 1023) asm volatile("trap;");
    asm volatile("fence.mbarrier_init.release.cluster;" ::: "memory");
    mbar_expect_tx(bdat, 32768); mbar_expect_tx(bdat + 8, 32768);
  }
  __syncthreads();
  asm volatile("barrier.cluster.arrive.release.aligned;\nbarrier.cluster.wait.acquire.aligned;" ::: "memory");
  const int mp = cid >> 3, tm1 = mp * 2 + rank, tn1 = cid & 7;
  const int tm2 = cid >> 2, tn2 = cid & 3;
  const int c0 = tn2 * 256 + rank * 128;

  if (wg == 2) {
    asm volatile("setmaxnreg.dec.sync.aligned.u32 56;");
    const int warp = (threadIdx.x >> 5) & 3, lane = threadIdx.x & 31;
    if (warp == 0) {
      if (lane == 0) {
        STAMP(0);
        uint32_t ph = 1;
#pragma unroll 1
        for (int it = 0; it < 32; it++) {
          int st = it & 3, t = it >> 4, kb = (it + (2 * mp & ~3)) & 15;
          uint32_t a = sb + st * STAGE, b = a + 16384;
          mbar_wait(bempty + st * 8, ph);
          mbar_expect_tx(bfull + st * 8, 16384 + B1BYTES);
          tma2d(a, &m_x, bfull + st * 8, kb * 64, tm1 * 128);
          tma3d_mc(b + rank * (B1BYTES / 2), &m_w1, bfull + st * 8, 0, kb * 64 + rank * 32, (tn1 + 8 * t) * 7, 3);
          if (st == 3) ph ^= 1;
        }
        mbar_wait(bdep, 0);
        fence_async();
#pragma unroll 1
        for (int st = 0; st < 4; st++) {
          mbar_wait(bempty + st * 8, ph);
          mbar_expect_tx(bfull + st * 8, 2 * CHB);
#pragma unroll 1
          for (int j = 0; j < 2; j++) {
            int ch = cta * 8 + st * 2 + j;
            uint32_t dst = sb + st * STAGE + j * CHB;
            bulk_g2s(dst, g_U + (size_t)ch * UCH, UCH, bfull + st * 8);
            bulk_g2s(dst + UCH, p.hk + (size_t)ch * S_, 4096, bfull + st * 8);
          }
        }
        ph ^= 1;
#pragma unroll 1
        for (int it = 0; it < 28; it++) {
          int st = it & 3;
          uint32_t a = sb + st * STAGE, b = a + 16384;
          int k0 = rank * 896 + it * 64 + (it >= 14 ? 896 : 0);
          if (it == 0 || it == 14) { if (it) STAMP(2); mbar_wait(bdep + (it ? 16 : 8), 0); fence_async(); if (it) STAMP(3); }
          mbar_wait(bempty + st * 8, ph);
          mbar_expect_tx(bfull + st * 8, STAGE);
          tma2d(a, &m_act, bfull + st * 8, k0, tm2 * 128);
#pragma unroll 1
          for (int j = 0; j < 4; j++) tma5d(b + j * 8192, &m_w2, bfull + st * 8, tn2 * 256 + ((j ^ (2 * (rank ^ 1))) * 64), k0 >> 5);
          if (it == 8) {
            mbar_expect_tx(bxt, 32768);
            tma2d(s_xt, &m_x, bxt, c0, tm2 * 128);
            tma2d(s_xt + 16384, &m_x, bxt, c0 + 64, tm2 * 128);
          }
          if (st == 3) ph ^= 1;
        }
        mbar_wait(bdep + 24, 0);
        fence_async();
        mbar_wait(bempty + 8, ph);
        mbar_expect_tx(bfull + 8, 32768);
        tma2d(sb + 65536, &m_y, bfull + 8, tm2 * 128, c0);
        tma2d(sb + 65536 + 16384, &m_y, bfull + 8, tm2 * 128 + 64, c0);
      }
    } else {
      if (warp == 1) {
#pragma unroll 1
        for (int t = 0; t < 2; t++) {
          const int n0 = (tn1 + 8 * t) * 224;
          bar_sync(NB_CS, 288);
          if (lane == 0) {
            if (t == 0) PSTAMP(24);
            signal(&g_cnt[(C_CS + tn1 + 8 * t) * 32]);
            if (t == 0) PSTAMP(27);
            wait_cnt(&g_cnt[(C_CS + tn1 + 8 * t) * 32], 16);
            if (t == 0) PSTAMP(28);
            fence_async();
            mbar_expect_tx(bhlp, 16 * 896);
#pragma unroll 1
            for (int j = 0; j < 16; j++) bulk_g2s(sb + (j >> 2) * STAGE + TAILOFF + (j & 3) * 896, g_csp + j * F_ + n0, 896, bhlp);
          }
          uint2 bb = *(const uint2*)(p.b1 + n0 + lane * 4), bb1 = bb;
          if (lane < 24) bb1 = *(const uint2*)(p.b1 + n0 + 128 + lane * 4);
          mbar_wait(bhlp, t);
          if (t == 0) PSTAMP(29);
#pragma unroll 1
          for (int h = 0; h < 2; h++) {
            int c = lane + 32 * h;
            if (c < 56) {
              float4 s = make_float4(0.f, 0.f, 0.f, 0.f);
#pragma unroll
              for (int j = 0; j < 16; j++) { float4 v = lds128(sb + (j >> 2) * STAGE + TAILOFF + (j & 3) * 896 + c * 16); s.x += v.x; s.y += v.y; s.z += v.z; s.w += v.w; }
              sts128(s_cb + c * 32, s.x, s.y, __uint_as_float(bb.x), 0.f);
              sts128(s_cb + c * 32 + 16, s.z, s.w, __uint_as_float(bb.y), 0.f);
            }
            bb = bb1;
          }
          __syncwarp();
          if (lane == 0) mbar_arrive(bepi);
          PSTAMP(25 + t);
        }
        if (lane == 0) { wait_cnt(&g_cnt[(C_U + (cta >> 2)) * 32], 8); mbar_arrive(bdep); }
        __syncwarp();
        bar_sync(NB_ACT, 288);
        if (lane == 0) { signal(&g_cnt[(C_ACT + tm1 * 2) * 32]); wait_cnt(&g_cnt[(C_ACT + tm2 * 2) * 32], 8); mbar_arrive(bdep + 8); }
        __syncwarp();
        bar_sync(NB_Y, 288);
        if (lane == 0) signal(&g_cnt[(C_Y + (cta >> 4)) * 32]);
        __syncwarp();
        bar_sync(NB_ACT, 288);
        if (lane == 0) {
          signal(&g_cnt[(C_ACT + tm1 * 2 + 1) * 32]);
          wait_cnt(&g_cnt[(C_ACT + tm2 * 2 + 1) * 32], 8);
          mbar_arrive(bdep + 16);
          fence_async();
          mbar_expect_tx(bepi, 1024);
          bulk_g2s(s_st, g_stat + tm2 * 128, 1024, bepi);
          wait_cnt(&g_cnt[(C_Y + tn2 * 2 + rank) * 32], 16);
          mbar_arrive(bdep + 24);
          unsigned tk = atomicAdd(&g_cnt[C_TK * 32], 1);
          if (tk == 127) {
#pragma unroll 1
            for (int i = 0; i <= C_TK; i++) g_cnt[i * 32] = 0;
          }
        }
      } else {
        const int cg = (cta & 15) * 2 + (warp - 2), tr = cta >> 4;
        const int ch = cg * 32 + (lane >> 1) * 2, vh = lane & 1;
        int T = tr * 256;
        const uint32_t buf = s_xt + (warp - 2) * 16384, bb = bkv + (warp - 2) * 16;
        if (lane == 0) {
          mbar_wait(bfull + 24, 0);
#pragma unroll 1
          for (int i = 0; i < 2; i++) {
            mbar_expect_tx(bb + i * 8, 8192);
            tma2d(buf + i * 8192, &m_k, bb + i * 8, cg * 32, T + i * 64);
            tma2d(buf + i * 8192 + 4096, &m_v, bb + i * 8, cg * 32, T + i * 64);
          }
        }
        __syncwarp();
        uint2 sa = *(const uint2*)(p.shk + ch * 4), sb2 = *(const uint2*)(p.shk + ch * 4 + 4);
        const uint32_t w0 = __byte_perm(sa.x, sb2.x, 0x5410), w1 = __byte_perm(sa.x, sb2.x, 0x7632), w2 = __byte_perm(sa.y, sb2.y, 0x5410), w3 = __byte_perm(sa.y, sb2.y, 0x7632);
        uint32_t km3 = 0, km2 = 0, km1 = 0, um1 = 0;
        if (T > 0) {
          const bf16* kp = p.k + (size_t)T * D_ + ch;
          uint32_t km4 = ldg32(kp - 4 * D_); km3 = ldg32(kp - 3 * D_); km2 = ldg32(kp - 2 * D_); km1 = ldg32(kp - D_);
          uint32_t vv = ldg32(p.v + (size_t)(T - 1) * D_ + ch);
          um1 = hmul2(hadd2(hadd2(hadd2(hmul2(km4, w3), hmul2(km3, w2)), hmul2(km2, w1)), hmul2(km1, w0)), vv);
        }
        uint8_t* ub = g_U + (size_t)ch * UCH + vh * 16;
#pragma unroll 1
        for (int c = 0; c < UITER; c++) {
          const int rd = c >> 3;
          if ((c & 7) == 0) mbar_wait(bb + (rd & 1) * 8, rd >> 1);
          const uint32_t src = buf + (rd & 1) * 8192 + (c & 7) * 512 + (lane >> 1) * 4;
          uint32_t kc[11], u[9];
          kc[0] = km3; kc[1] = km2; kc[2] = km1; u[0] = um1;
#pragma unroll
          for (int i = 0; i < 8; i++) { kc[3 + i] = lds32(src + i * 64); u[1 + i] = lds32(src + 4096 + i * 64); }
#pragma unroll
          for (int i = 0; i < 8; i++) u[1 + i] = hmul2(hadd2(hadd2(hadd2(hmul2(kc[i], w3), hmul2(kc[i + 1], w2)), hmul2(kc[i + 2], w1)), hmul2(kc[i + 3], w0)), u[1 + i]);
          km3 = kc[8]; km2 = kc[9]; km1 = kc[10]; um1 = u[8];
#pragma unroll
          for (int i = 0; i < 8; i++) u[i] = vh ? u[i + 1] : u[i];
          int kap = (2040 - T) >> 3;
          uint8_t* rec = ub + (kap & 3) * UARR + (kap >> 2) * 32;
          stg128(rec, __byte_perm(u[7], u[6], 0x5410), __byte_perm(u[5], u[4], 0x5410), __byte_perm(u[3], u[2], 0x5410), __byte_perm(u[1], u[0], 0x5410));
          stg128(rec + UCH, __byte_perm(u[7], u[6], 0x7632), __byte_perm(u[5], u[4], 0x7632), __byte_perm(u[3], u[2], 0x7632), __byte_perm(u[1], u[0], 0x7632));
          if ((c & 7) == 7 && rd < 2) {
            __syncwarp();
            if (lane == 0) {
              mbar_expect_tx(bb + (rd & 1) * 8, 8192);
              tma2d(buf + (rd & 1) * 8192, &m_k, bb + (rd & 1) * 8, cg * 32, T + 72);
              tma2d(buf + (rd & 1) * 8192 + 4096, &m_v, bb + (rd & 1) * 8, cg * 32, T + 72);
            }
          }
          T += 8;
        }
        if (tr == 0) {
#pragma unroll 1
          for (int i = 0; i < 32; i++) stg128(g_U + (size_t)(cg * 32 + i) * UCH + (lane >> 3) * UARR + 2048 + (lane & 7) * 16, 0, 0, 0, 0);
        }
        __syncwarp();
        PSTAMP(30 + warp);
        if (lane == 0) signal(&g_cnt[(C_U + cg) * 32]);
        PSTAMP(28 + warp);
      }
    }
  } else {
    asm volatile("setmaxnreg.inc.sync.aligned.u32 224;");
    const int lane = threadIdx.x & 31, w = (threadIdx.x >> 5) & 3, g = lane >> 2, q = lane & 3;
    const bool leader = (threadIdx.x & 127) == 0;
    uint32_t hp[56];
    bf16* ap = g_act + (size_t)(tm1 * 128 + wg * 64 + w * 16 + g) * F_ + tn1 * 224 + q * 8;
    {
      const uint32_t e0 = mapa(bempty, 0), e1 = mapa(bempty, 1);
      const uint64_t da0 = mkdesc(sb + wg * 8192, 16, 1024, 1), db0 = mkdesc(sb + 16384, 2048, 512, 2);
      float rc = 0.f, rs1 = 0.f, rs2 = 0.f, cs0 = 0.f, cs1 = 0.f;
      float2 st0, st1;
      const int W = rank * 56 + w * 16 + (lane & 15);
      const uint32_t csb = sb + 16384 + wg * (B1BYTES / 2) + (W >> 4) * 2048 + (lane >> 4) * 64 + (W & 3) * 4;
      const uint32_t rsb = sb + (wg * 64 + w * 16 + (lane >> 1)) * 128 + (lane & 1) * 64;
#pragma unroll 1
      for (uint32_t t = 0; t < 2; t++) {
        float d[112];
#pragma unroll 1
        for (uint32_t kb = 0; kb < 16; kb++) {
          const uint32_t st = kb & 3, so = st * STAGE;
          mbar_wait(bfull + st * 8, (kb >> 2) & 1);
          if (t == 0 && kb == 0) STAMP(4 + wg);
          const uint64_t da = da0 + (so >> 4), db = db0 + (so >> 4);
          wg_fence();
#pragma unroll
          for (int kk = 0; kk < 4; kk++) mma_n224(d, da + kk * 2, db + (((kk & 1) * 1024 + (kk >> 1) * (B1BYTES / 2)) >> 4), kk || kb);
          wg_commit();
          wg_wait<1>();
          if (kb && lane == 0) { mbar_arrive_remote(e0 + ((kb - 1) & 3) * 8); mbar_arrive_remote(e1 + ((kb - 1) & 3) * 8); }
          if ((kb >> 1) == (mp & 1)) {
            if (w < 3 || (lane & 15) < 8) {
#pragma unroll
              for (int r = 0; r < 16; r++) {
                uint32_t v = lds32(csb + so + r * 128 + ((((W >> 2) ^ r) & 3) << 4));
                cs0 += blo(v); cs1 += bhi(v);
              }
            }
            if (kb & 1) {
              cs0 += __shfl_xor_sync(0xffffffff, cs0, 16); cs1 += __shfl_xor_sync(0xffffffff, cs1, 16);
              if (lane < (w < 3 ? 16 : 8)) *(float2*)(g_csp + (mp * 2 + wg) * F_ + (tn1 + 8 * t) * 224 + W * 2) = make_float2(cs0, cs1);
              bar_arrive(NB_CS, 288);
              cs0 = 0.f; cs1 = 0.f;
            }
          }
          if (t == XROW) {
#pragma unroll
            for (int i = 0; i < 4; i++) {
              float4 v = lds128(rsb + so + ((i ^ ((lane >> 1) & 3)) << 4));
              const uint32_t vw[4] = {__float_as_uint(v.x), __float_as_uint(v.y), __float_as_uint(v.z), __float_as_uint(v.w)};
              if (i == 0 && kb == 0) rc = blo(vw[0]);
#pragma unroll
              for (int j = 0; j < 4; j++) { float a = blo(vw[j]) - rc, b = bhi(vw[j]) - rc; rs1 += a; rs2 = fmaf(a, a, rs2); rs1 += b; rs2 = fmaf(b, b, rs2); }
            }
          } else if (kb >= XCH && t == 1) {
            act_chunk<1>(hp, ap + (kb & 1) * 8 * F_ + ((kb - 2) >> 1) * 32);
          }
        }
        if (t == 0) {
          float m = rc + rs1 * (1.f / 512), m2 = rs2 - rs1 * rs1 * (1.f / 512);
          float mo = __shfl_xor_sync(0xffffffff, m, 1), m2o = __shfl_xor_sync(0xffffffff, m2, 1);
          float var = fmaxf((m2 + m2o + (m - mo) * (m - mo) * 256.f) * (1.f / D_), 0.f), sq;
          asm("sqrt.approx.ftz.f32 %0, %1;" : "=f"(sq) : "f"(rbf(rbf(var) + 1e-5f)));
          float mb = rbf(0.5f * (m + mo)), rs = rcp(rbf(sq));
          if (tn1 == 0 && !(lane & 1)) g_stat[tm1 * 128 + wg * 64 + w * 16 + (lane >> 1)] = make_float2(mb, rs);
          st0.x = __shfl_sync(0xffffffff, mb, 2 * g); st0.y = __shfl_sync(0xffffffff, rs, 2 * g);
          st1.x = __shfl_sync(0xffffffff, mb, 2 * g + 16); st1.y = __shfl_sync(0xffffffff, rs, 2 * g + 16);
        } else {
          bar_arrive(NB_ACT, 288);
        }
        wg_wait<0>();
        if (lane == 0) { mbar_arrive_remote(e0 + 24); mbar_arrive_remote(e1 + 24); }
        STAMP(6 + 4 * t + wg);
        mbar_wait(bepi, t);
#pragma unroll
        for (int j = 0; j < 28; j++) {
          float4 cb = lds128(s_cb + j * 64 + q * 16);
          uint32_t bias = __float_as_uint(cb.z);
          hp[(j >> 2) * 8 + (j & 3)] = hadd2(pack2((d[4 * j] - st0.x * cb.x) * st0.y, (d[4 * j + 1] - st0.x * cb.y) * st0.y), bias);
          hp[(j >> 2) * 8 + 4 + (j & 3)] = hadd2(pack2((d[4 * j + 2] - st1.x * cb.x) * st1.y, (d[4 * j + 3] - st1.x * cb.y) * st1.y), bias);
        }
        STAMP(8 + 4 * t + wg);
      }
      ap += 8 * 224;
    }
    {
      float d[4][16];
      uint32_t xa[16], xb[16], xc[16];
      uint32_t uoff[2], xoff[3], xok = 0;
      const uint32_t zr = p.zero;
      const uint32_t xbuf = sb + (2 + wg) * STAGE + XOFF + lane * 16;
#pragma unroll
      for (int hh = 0; hh < 2; hh++) { int x = 2046 - (128 * w + 32 * (3 - q) + 2 * g + 16 * hh); int kap = x >> 3; uoff[hh] = (kap & 3) * UARR + (kap >> 2) * 32 + 16 + (x & 7) * 2; }
#pragma unroll
      for (int dw = 1; dw < 4; dw++) {
        int w2 = (w + dw) & 3, i2 = 15 + w2 - w;
        if (i2 <= 15) xok |= 1u << dw;
        xoff[dw - 1] = xbuf + (w2 * 11 - (w2 * (w2 - 1)) / 2 + (i2 >> 2) * 3 + (i2 & 3)) * 512;
      }
      const uint32_t xb_w = xbuf + (w * 11 - (w * (w - 1)) / 2) * 512;
      if (wg == 1) bar_arrive(NB_ORD0, 256);
#pragma unroll 1
      for (int it = 0; it < 4; it++) {
        int ch = cta * 8 + it * 2 + wg;
        uint32_t ub = sb + it * STAGE + wg * CHB, hb = ub + UCH - 64 + (w * 64 + g + q + 1) * 4;
        uint64_t dbs = mkdesc(ub, UARR, 128, 0);
        float dval = __bfloat162float(p.Dv[ch]);
        mbar_wait(bfull + it * 8, 0);
        loadA<0>(xa, hb); loadA<1>(xb, hb); loadA<2>(xc, hb);
        uint32_t uu[8];
#pragma unroll
        for (int a = 0; a < 4; a++)
#pragma unroll
          for (int hh = 0; hh < 2; hh++) uu[2 * a + hh] = lds32(ub + uoff[hh] - a * 512);
        dupA(xa, zr); dupA(xb, zr); dupA(xc, zr);
        bar_sync(NB_ORD0 + wg, 256);
        mmaG<0>(d, xa, dbs);
        mmaG<1>(d, xb, dbs);
        wg_wait<1>(); loadA<3>(xa, hb); mmaG<2>(d, xc, dbs); dupA(xa, zr);
        wg_wait<1>(); loadA<4>(xb, hb); mmaG<3>(d, xa, dbs); dupA(xb, zr);
        wg_wait<1>(); loadA<5>(xc, hb); mmaG<4>(d, xb, dbs); dupA(xc, zr);
        wg_wait<1>(); loadA<6>(xa, hb); mmaG<5>(d, xc, dbs); dupA(xa, zr);
        wg_wait<1>(); loadA<7>(xb, hb); mmaG<6>(d, xa, dbs); dupA(xb, zr);
        mmaG<7>(d, xb, dbs);
        if (!(it == 3 && wg == 1)) bar_arrive(NB_ORD0 + (wg ^ 1), 256);
        wg_wait<0>();
        if (it == 0) mbar_wait(bfull + (2 + wg) * 8, 0);
        bar_sync(NB_WG0 + wg, 128);
        if (leader && it != 2 + wg) mbar_arrive8(bempty + it * 8);
#pragma unroll
        for (int i = 0; i < 16; i++)
          if ((i & 3) != 3) {
            if (i >= 3 || i >= w) sts128(xb_w + ((i >> 2) * 3 + (i & 3)) * 512, d[i >> 2][4 * (i & 3)], d[i >> 2][4 * (i & 3) + 1], d[i >> 2][4 * (i & 3) + 2], d[i >> 2][4 * (i & 3) + 3]);
          }
        bar_sync(NB_WG0 + wg, 128);
        bf16* yp = g_Y + (size_t)ch * S_ + 128 * w + 32 * (3 - q) + 2 * g;
#pragma unroll
        for (int a = 0; a < 4; a++) {
          float s0 = d[3 - a][12], s1 = d[3 - a][13], s2 = d[3 - a][14], s3 = d[3 - a][15];
#pragma unroll
          for (int dw = 1; dw < 4; dw++)
            if (a > 0 || (xok >> dw) & 1) { float4 t = lds128(xoff[dw - 1] - a * 3 * 512); s0 += t.x; s1 += t.y; s2 += t.z; s3 += t.w; }
#pragma unroll
          for (int hh = 0; hh < 2; hh++) {
            uint32_t u2 = uu[2 * a + hh];
            float y0 = hh ? s2 : s0, y1 = hh ? s3 : s1;
            *(uint32_t*)(yp + 512 * a + 16 * hh) = hadd2(pack2(y0, y1), pack2(bhi(u2) * dval, blo(u2) * dval));
          }
        }
      }
      bar_arrive(NB_Y, 288);
      bar_sync(NB_WG0 + wg, 128);
      if (leader) mbar_arrive8(bempty + (2 + wg) * 8);
    }
    STAMP(14 + wg);
    {
      float d[128];
      const uint64_t da0 = mkdesc(sb + wg * 8192, 16, 1024, 1), db0 = mkdesc(sb + 16384, 8192, 1024, 1);
      auto kstep = [&](uint32_t kb) {
        const uint32_t st = kb & 3, so = st * (STAGE >> 4);
        mbar_wait(bfull + st * 8, ((kb >> 2) & 1) ^ 1);
        wg_fence();
#pragma unroll
        for (int kk = 0; kk < 4; kk++) mma_n256(d, da0 + (so + kk * 2), db0 + (so + kk * 128), kk || kb);
        wg_commit();
        wg_wait<1>();
        if (kb && leader) mbar_arrive8(bempty + ((kb - 1) & 3) * 8);
      };
#pragma unroll 1
      for (uint32_t kb = 0; kb < 7; kb++) {
        kstep(kb);
        if (kb == 0) STAMP(40 + wg);
        act_chunk<2>(hp, ap + kb * 32);
      }
      bar_arrive(NB_ACT, 288);
      STAMP(42 + wg);
#pragma unroll 1
      for (uint32_t kb = 7; kb < 28; kb++) {
        kstep(kb);
        if ((kb & 3) == 3) STAMP(44 + (kb >> 2) * 2 + wg);
        if (kb == 26 && leader) mbar_arrive_remote(mapa(brdy, rank ^ 1));
      }
      wg_wait<0>();
      STAMP(16 + wg);
      mbar_wait_cluster(brdy, 0);
      {
        uint32_t dst = mapa(sb + wg * 32768 + (threadIdx.x & 127) * 16, rank ^ 1), rb = mapa(bdat + wg * 8, rank ^ 1);
#pragma unroll
        for (int j = 0; j < 16; j++)
          asm volatile("st.async.shared::cluster.mbarrier::complete_tx::bytes.v4.f32 [%0], {%1,%2,%3,%4}, [%5];" ::"r"(dst + j * 2048), "f"(d[4 * j]), "f"(d[4 * j + 1]), "f"(d[4 * j + 2]), "f"(d[4 * j + 3]), "r"(rb) : "memory");
      }
      STAMP(22 + wg);
      mbar_wait(bxt, 0);
      mbar_wait(bepi, 0);
      mbar_wait(bfull + 8, 0);
      const int mr = lane & 7, mi = lane >> 3;
      const uint32_t xrow = s_xt + (wg * 64 + w * 16 + (mi & 1) * 8 + mr) * 128;
      uint32_t xr[32], sr[32];
      {
        float2 st0, st1;
        asm volatile("ld.shared.v2.f32 {%0,%1}, [%2];" : "=f"(st0.x), "=f"(st0.y) : "r"(s_st + (wg * 64 + w * 16 + g) * 8));
        asm volatile("ld.shared.v2.f32 {%0,%1}, [%2];" : "=f"(st1.x), "=f"(st1.y) : "r"(s_st + (wg * 64 + w * 16 + g + 8) * 8));
        const uint32_t nm[2] = {pack2(-st0.x, -st0.x), pack2(-st1.x, -st1.x)};
        const float rs[2] = {st0.y, st1.y};
#pragma unroll
        for (int jp = 0; jp < 8; jp++) {
          uint32_t xa = xrow + (jp >> 2) * 16384 + ((((jp & 3) * 2 + (mi >> 1)) ^ mr) << 4);
          uint32_t ya = sb + 65536 + wg * 16384 + (jp * 16 + (mi >> 1) * 8 + mr) * 128 + (((w * 2 + (mi & 1)) ^ mr) << 4);
          uint32_t yr[4];
          asm volatile("ldmatrix.sync.aligned.m8n8.x4.shared.b16 {%0,%1,%2,%3}, [%4];" : "=r"(xr[4 * jp]), "=r"(xr[4 * jp + 1]), "=r"(xr[4 * jp + 2]), "=r"(xr[4 * jp + 3]) : "r"(xa) : "memory");
          asm volatile("ldmatrix.sync.aligned.m8n8.x4.trans.shared.b16 {%0,%1,%2,%3}, [%4];" : "=r"(yr[0]), "=r"(yr[1]), "=r"(yr[2]), "=r"(yr[3]) : "r"(ya) : "memory");
#pragma unroll
          for (int m = 0; m < 4; m++) {
            uint32_t xc = hadd2(xr[4 * jp + m], nm[m & 1]);
            sr[4 * jp + m] = hmul2(pack2(blo(xc) * rs[m & 1], bhi(xc) * rs[m & 1]), yr[m]);
          }
        }
      }
      mbar_wait_cluster(bdat + wg * 8, 0);
      STAMP(18 + wg);
      const uint32_t src = sb + wg * 32768 + (threadIdx.x & 127) * 16;
#pragma unroll
      for (int jp = 0; jp < 8; jp++) {
        uint32_t o[4];
#pragma unroll
        for (int c = 0; c < 2; c++) {
          int j = jp * 2 + c;
          float4 r = lds128(src + j * 2048);
          float z[4] = {d[64 + 4 * j] + r.x, d[64 + 4 * j + 1] + r.y, d[64 + 4 * j + 2] + r.z, d[64 + 4 * j + 3] + r.w};
#pragma unroll
          for (int hh = 0; hh < 2; hh++) {
            uint32_t zp = pack2(z[2 * hh], z[2 * hh + 1]);
            int m = c * 2 + hh;
            o[m] = hadd2(xr[4 * jp + m], hmul2(sr[4 * jp + m], pack2(silu(blo(zp)), silu(bhi(zp)))));
          }
        }
        uint32_t xa = xrow + (jp >> 2) * 16384 + ((((jp & 3) * 2 + (mi >> 1)) ^ mr) << 4);
        asm volatile("stmatrix.sync.aligned.m8n8.x4.shared.b16 [%0], {%1,%2,%3,%4};" ::"r"(xa), "r"(o[0]), "r"(o[1]), "r"(o[2]), "r"(o[3]) : "memory");
      }
      asm volatile("fence.proxy.async.shared::cta;" ::: "memory");
      bar_sync(NB_WG0 + wg, 128);
      if (leader) {
        tma2d_store(&m_out, s_xt + wg * 8192, c0, tm2 * 128 + wg * 64);
        tma2d_store(&m_out, s_xt + 16384 + wg * 8192, c0 + 64, tm2 * 128 + wg * 64);
        asm volatile("cp.async.bulk.commit_group;" ::: "memory");
        asm volatile("cp.async.bulk.wait_group.read 0;" ::: "memory");
      }
      STAMP(20 + wg);
    }
  }
}

typedef CUresult (*EncFn)(CUtensorMap*, CUtensorMapDataType, cuuint32_t, void*, const cuuint64_t*, const cuuint64_t*, const cuuint32_t*, const cuuint32_t*,
                          CUtensorMapInterleave, CUtensorMapSwizzle, CUtensorMapL2promotion, CUtensorMapFloatOOBfill);
static CUtensorMap mkmap(EncFn enc, const void* ptr, int rank, const uint64_t* dims, const uint64_t* strides, const uint32_t* box, CUtensorMapSwizzle sw) {
  CUtensorMap m;
  uint32_t es[5] = {1, 1, 1, 1, 1};
  enc(&m, CU_TENSOR_MAP_DATA_TYPE_BFLOAT16, rank, (void*)ptr, (const cuuint64_t*)dims, (const cuuint64_t*)strides, box, es, CU_TENSOR_MAP_INTERLEAVE_NONE, sw,
      CU_TENSOR_MAP_L2_PROMOTION_L2_256B, CU_TENSOR_MAP_FLOAT_OOB_FILL_NONE);
  return m;
}

extern "C" void kernel_launch(void* const* d_in, const int* in_sizes, int n_in, void* d_out, int out_size) {
  void* fn = nullptr;
  cudaDriverEntryPointQueryResult qr;
  cudaGetDriverEntryPoint("cuTensorMapEncodeTiled", &fn, cudaEnableDefault, &qr);
  EncFn enc = (EncFn)fn;
  void *act, *Y;
  cudaGetSymbolAddress(&act, g_act); cudaGetSymbolAddress(&Y, g_Y);
  uint64_t dx[2] = {D_, S_}, sx[1] = {D_ * 2};
  uint32_t b128[2] = {64, 128}, b64[2] = {64, 64};
  CUtensorMap m_x = mkmap(enc, d_in[0], 2, dx, sx, b128, CU_TENSOR_MAP_SWIZZLE_128B);
  CUtensorMap m_out = mkmap(enc, d_out, 2, dx, sx, b64, CU_TENSOR_MAP_SWIZZLE_128B);
  uint64_t dw1[3] = {32, D_, F_ / 32}, sw1[2] = {F_ * 2, 64};
  uint32_t bw1[3] = {32, 32, 7};
  CUtensorMap m_w1 = mkmap(enc, d_in[7], 3, dw1, sw1, bw1, CU_TENSOR_MAP_SWIZZLE_64B);
  uint64_t da[2] = {F_, S_}, sa[1] = {F_ * 2};
  CUtensorMap m_act = mkmap(enc, act, 2, da, sa, b128, CU_TENSOR_MAP_SWIZZLE_128B);
  uint64_t dw2[5] = {D_, 2, 4, 4, F_ / 32}, sw2[4] = {D_ * 2, 8 * D_ * 2, 2 * D_ * 2, 32 * D_ * 2};
  uint32_t bw2[5] = {64, 2, 4, 4, 2};
  CUtensorMap m_w2 = mkmap(enc, d_in[9], 5, dw2, sw2, bw2, CU_TENSOR_MAP_SWIZZLE_128B);
  uint64_t dy[2] = {S_, D_}, sy[1] = {S_ * 2};
  CUtensorMap m_y = mkmap(enc, Y, 2, dy, sy, b128, CU_TENSOR_MAP_SWIZZLE_128B);
  uint32_t bkv[2] = {32, 64};
  CUtensorMap m_k = mkmap(enc, d_in[1], 2, dx, sx, bkv, CU_TENSOR_MAP_SWIZZLE_NONE);
  CUtensorMap m_v = mkmap(enc, d_in[2], 2, dx, sx, bkv, CU_TENSOR_MAP_SWIZZLE_NONE);
  Params p;
  p.x = (const bf16*)d_in[0]; p.k = (const bf16*)d_in[1]; p.v = (const bf16*)d_in[2]; p.shk = (const bf16*)d_in[3];
  p.hk = (const bf16*)d_in[4]; p.Dv = (const bf16*)d_in[5]; p.b1 = (const bf16*)d_in[8]; p.zero = 0;
  cudaFuncSetAttribute(fused_kernel, cudaFuncAttributeMaxDynamicSharedMemorySize, SMEM_BYTES);
  fused_kernel<<<128, 384, SMEM_BYTES, cudaStreamPerThread>>>(m_x, m_w1, m_act, m_w2, m_y, m_out, m_k, m_v, p);
}
```

```cpp
#include <cuda_runtime.h>
#include <cuda.h>
#include <cuda_bf16.h>
#include <stdint.h>

typedef __nv_bfloat16 bf16;
typedef __nv_bfloat162 bf162;
constexpr int S_ = 2048, D_ = 1024, F_ = 3584;
constexpr int UARR = 2176, UCH = 2 * UARR;
constexpr int CU0 = 64, CH0 = CU0 + UARR, CU1 = CH0 + 4096 + 64, CH1 = CU1 + UARR, CHB = CH1 + 4096;
constexpr int STAGE = 49152, NST = 4;
constexpr int XOFF = 2 * CHB;
constexpr int SM_XT = NST * STAGE;
constexpr int SM_ST = SM_XT + 32768;
constexpr int SM_CB = SM_ST + 1024;
constexpr int SM_BARS = SM_CB + 1792;
constexpr int SMEM_BYTES = SM_BARS + 256;
constexpr int B1BYTES = 224 * 64 * 2;

__device__ __align__(1024) uint4 g_stat[S_];
__device__ __align__(1024) float g_csp[8 * 16 * 256];
__device__ __align__(1024) bf16 g_act[S_ * F_];
__device__ __align__(1024) uint8_t g_U[(size_t)D_ * UCH];
__device__ __align__(1024) bf16 g_Y[D_ * S_];
__device__ __align__(1024) uint4 g_xch[128 * 8 * 256];
enum { C_U = 0, C_ACT = 16, C_Y = 144, C_TK = 152 };
__device__ unsigned g_cnt[(C_TK + 1) * 32];
#define STAMP(i)
#define STAMP0(i)
#define PSTAMP(i)

#define UITER 16
#define MAPM 1
#define LOHI 0
#define UWAIT 4
#define UMASK 0x6600
#define HKL 0
#define UW2 2
#define KVK 20
#define W1K 20
#define HKPF 40
#define XPF 3
#define POLLJ 2
#define POLLNS 50
#define PARTX (MAPM ? 64 : 8)
__device__ __forceinline__ void mma_n224(float (&d)[112], uint32_t da, uint32_t db, int sd) {
  asm volatile("{\n.reg .pred p;\n.reg .b64 a, b;\nsetp.ne.b32 p, %114, 0;\nmov.b64 a, {%112, 0x40000040};\nmov.b64 b, {%113, 0x80000020};\n"
    "wgmma.mma_async.sync.aligned.m64n224k16.f32.bf16.bf16 {%0,%1,%2,%3,%4,%5,%6,%7,%8,%9,%10,%11,%12,%13,%14,%15,%16,%17,%18,%19,%20,%21,%22,%23,%24,%25,%26,%27,%28,%29,%30,%31,%32,%33,%34,%35,%36,%37,%38,%39,%40,%41,%42,%43,%44,%45,%46,%47,%48,%49,%50,%51,%52,%53,%54,%55,%56,%57,%58,%59,%60,%61,%62,%63,%64,%65,%66,%67,%68,%69,%70,%71,%72,%73,%74,%75,%76,%77,%78,%79,%80,%81,%82,%83,%84,%85,%86,%87,%88,%89,%90,%91,%92,%93,%94,%95,%96,%97,%98,%99,%100,%101,%102,%103,%104,%105,%106,%107,%108,%109,%110,%111}, a, b, p, 1, 1, 0, 1;\n}\n"
    : "+f"(d[0]),"+f"(d[1]),"+f"(d[2]),"+f"(d[3]),"+f"(d[4]),"+f"(d[5]),"+f"(d[6]),"+f"(d[7]),"+f"(d[8]),"+f"(d[9]),"+f"(d[10]),"+f"(d[11]),"+f"(d[12]),"+f"(d[13]),"+f"(d[14]),"+f"(d[15]),"+f"(d[16]),"+f"(d[17]),"+f"(d[18]),"+f"(d[19]),"+f"(d[20]),"+f"(d[21]),"+f"(d[22]),"+f"(d[23]),"+f"(d[24]),"+f"(d[25]),"+f"(d[26]),"+f"(d[27]),"+f"(d[28]),"+f"(d[29]),"+f"(d[30]),"+f"(d[31]),"+f"(d[32]),"+f"(d[33]),"+f"(d[34]),"+f"(d[35]),"+f"(d[36]),"+f"(d[37]),"+f"(d[38]),"+f"(d[39]),"+f"(d[40]),"+f"(d[41]),"+f"(d[42]),"+f"(d[43]),"+f"(d[44]),"+f"(d[45]),"+f"(d[46]),"+f"(d[47]),"+f"(d[48]),"+f"(d[49]),"+f"(d[50]),"+f"(d[51]),"+f"(d[52]),"+f"(d[53]),"+f"(d[54]),"+f"(d[55]),"+f"(d[56]),"+f"(d[57]),"+f"(d[58]),"+f"(d[59]),"+f"(d[60]),"+f"(d[61]),"+f"(d[62]),"+f"(d[63]),"+f"(d[64]),"+f"(d[65]),"+f"(d[66]),"+f"(d[67]),"+f"(d[68]),"+f"(d[69]),"+f"(d[70]),"+f"(d[71]),"+f"(d[72]),"+f"(d[73]),"+f"(d[74]),"+f"(d[75]),"+f"(d[76]),"+f"(d[77]),"+f"(d[78]),"+f"(d[79]),"+f"(d[80]),"+f"(d[81]),"+f"(d[82]),"+f"(d[83]),"+f"(d[84]),"+f"(d[85]),"+f"(d[86]),"+f"(d[87]),"+f"(d[88]),"+f"(d[89]),"+f"(d[90]),"+f"(d[91]),"+f"(d[92]),"+f"(d[93]),"+f"(d[94]),"+f"(d[95]),"+f"(d[96]),"+f"(d[97]),"+f"(d[98]),"+f"(d[99]),"+f"(d[100]),"+f"(d[101]),"+f"(d[102]),"+f"(d[103]),"+f"(d[104]),"+f"(d[105]),"+f"(d[106]),"+f"(d[107]),"+f"(d[108]),"+f"(d[109]),"+f"(d[110]),"+f"(d[111])
    : "r"(da), "r"(db), "r"(sd));
}
__device__ __forceinline__ void mma_n256(float (&d)[128], uint32_t da, uint32_t db, int sd) {
  asm volatile("{\n.reg .pred p;\n.reg .b64 a, b;\nsetp.ne.b32 p, %130, 0;\nmov.b64 a, {%128, 0x40000040};\nmov.b64 b, {%129, 0x40000040};\n"
    "wgmma.mma_async.sync.aligned.m64n256k16.f32.bf16.bf16 {%0,%1,%2,%3,%4,%5,%6,%7,%8,%9,%10,%11,%12,%13,%14,%15,%16,%17,%18,%19,%20,%21,%22,%23,%24,%25,%26,%27,%28,%29,%30,%31,%32,%33,%34,%35,%36,%37,%38,%39,%40,%41,%42,%43,%44,%45,%46,%47,%48,%49,%50,%51,%52,%53,%54,%55,%56,%57,%58,%59,%60,%61,%62,%63,%64,%65,%66,%67,%68,%69,%70,%71,%72,%73,%74,%75,%76,%77,%78,%79,%80,%81,%82,%83,%84,%85,%86,%87,%88,%89,%90,%91,%92,%93,%94,%95,%96,%97,%98,%99,%100,%101,%102,%103,%104,%105,%106,%107,%108,%109,%110,%111,%112,%113,%114,%115,%116,%117,%118,%119,%120,%121,%122,%123,%124,%125,%126,%127}, a, b, p, 1, 1, 0, 1;\n}\n"
    : "+f"(d[0]),"+f"(d[1]),"+f"(d[2]),"+f"(d[3]),"+f"(d[4]),"+f"(d[5]),"+f"(d[6]),"+f"(d[7]),"+f"(d[8]),"+f"(d[9]),"+f"(d[10]),"+f"(d[11]),"+f"(d[12]),"+f"(d[13]),"+f"(d[14]),"+f"(d[15]),"+f"(d[16]),"+f"(d[17]),"+f"(d[18]),"+f"(d[19]),"+f"(d[20]),"+f"(d[21]),"+f"(d[22]),"+f"(d[23]),"+f"(d[24]),"+f"(d[25]),"+f"(d[26]),"+f"(d[27]),"+f"(d[28]),"+f"(d[29]),"+f"(d[30]),"+f"(d[31]),"+f"(d[32]),"+f"(d[33]),"+f"(d[34]),"+f"(d[35]),"+f"(d[36]),"+f"(d[37]),"+f"(d[38]),"+f"(d[39]),"+f"(d[40]),"+f"(d[41]),"+f"(d[42]),"+f"(d[43]),"+f"(d[44]),"+f"(d[45]),"+f"(d[46]),"+f"(d[47]),"+f"(d[48]),"+f"(d[49]),"+f"(d[50]),"+f"(d[51]),"+f"(d[52]),"+f"(d[53]),"+f"(d[54]),"+f"(d[55]),"+f"(d[56]),"+f"(d[57]),"+f"(d[58]),"+f"(d[59]),"+f"(d[60]),"+f"(d[61]),"+f"(d[62]),"+f"(d[63]),"+f"(d[64]),"+f"(d[65]),"+f"(d[66]),"+f"(d[67]),"+f"(d[68]),"+f"(d[69]),"+f"(d[70]),"+f"(d[71]),"+f"(d[72]),"+f"(d[73]),"+f"(d[74]),"+f"(d[75]),"+f"(d[76]),"+f"(d[77]),"+f"(d[78]),"+f"(d[79]),"+f"(d[80]),"+f"(d[81]),"+f"(d[82]),"+f"(d[83]),"+f"(d[84]),"+f"(d[85]),"+f"(d[86]),"+f"(d[87]),"+f"(d[88]),"+f"(d[89]),"+f"(d[90]),"+f"(d[91]),"+f"(d[92]),"+f"(d[93]),"+f"(d[94]),"+f"(d[95]),"+f"(d[96]),"+f"(d[97]),"+f"(d[98]),"+f"(d[99]),"+f"(d[100]),"+f"(d[101]),"+f"(d[102]),"+f"(d[103]),"+f"(d[104]),"+f"(d[105]),"+f"(d[106]),"+f"(d[107]),"+f"(d[108]),"+f"(d[109]),"+f"(d[110]),"+f"(d[111]),"+f"(d[112]),"+f"(d[113]),"+f"(d[114]),"+f"(d[115]),"+f"(d[116]),"+f"(d[117]),"+f"(d[118]),"+f"(d[119]),"+f"(d[120]),"+f"(d[121]),"+f"(d[122]),"+f"(d[123]),"+f"(d[124]),"+f"(d[125]),"+f"(d[126]),"+f"(d[127])
    : "r"(da), "r"(db), "r"(sd));
}
__device__ __forceinline__ void mma_n128lo(float (&d)[128], uint32_t da, uint32_t db, int sd) {
  asm volatile("{\n.reg .pred p;\n.reg .b64 a, b;\nsetp.ne.b32 p, %66, 0;\nmov.b64 a, {%64, 0x40000040};\nmov.b64 b, {%65, 0x40000040};\n"
    "wgmma.mma_async.sync.aligned.m64n128k16.f32.bf16.bf16 {%0,%1,%2,%3,%4,%5,%6,%7,%8,%9,%10,%11,%12,%13,%14,%15,%16,%17,%18,%19,%20,%21,%22,%23,%24,%25,%26,%27,%28,%29,%30,%31,%32,%33,%34,%35,%36,%37,%38,%39,%40,%41,%42,%43,%44,%45,%46,%47,%48,%49,%50,%51,%52,%53,%54,%55,%56,%57,%58,%59,%60,%61,%62,%63}, a, b, p, 1, 1, 0, 1;\n}\n"
    : "+f"(d[0]),"+f"(d[1]),"+f"(d[2]),"+f"(d[3]),"+f"(d[4]),"+f"(d[5]),"+f"(d[6]),"+f"(d[7]),"+f"(d[8]),"+f"(d[9]),"+f"(d[10]),"+f"(d[11]),"+f"(d[12]),"+f"(d[13]),"+f"(d[14]),"+f"(d[15]),"+f"(d[16]),"+f"(d[17]),"+f"(d[18]),"+f"(d[19]),"+f"(d[20]),"+f"(d[21]),"+f"(d[22]),"+f"(d[23]),"+f"(d[24]),"+f"(d[25]),"+f"(d[26]),"+f"(d[27]),"+f"(d[28]),"+f"(d[29]),"+f"(d[30]),"+f"(d[31]),"+f"(d[32]),"+f"(d[33]),"+f"(d[34]),"+f"(d[35]),"+f"(d[36]),"+f"(d[37]),"+f"(d[38]),"+f"(d[39]),"+f"(d[40]),"+f"(d[41]),"+f"(d[42]),"+f"(d[43]),"+f"(d[44]),"+f"(d[45]),"+f"(d[46]),"+f"(d[47]),"+f"(d[48]),"+f"(d[49]),"+f"(d[50]),"+f"(d[51]),"+f"(d[52]),"+f"(d[53]),"+f"(d[54]),"+f"(d[55]),"+f"(d[56]),"+f"(d[57]),"+f"(d[58]),"+f"(d[59]),"+f"(d[60]),"+f"(d[61]),"+f"(d[62]),"+f"(d[63])
    : "r"(da), "r"(db), "r"(sd));
}
__device__ __forceinline__ void mma_n128hi(float (&d)[128], uint32_t da, uint32_t db, int sd) {
  asm volatile("{\n.reg .pred p;\n.reg .b64 a, b;\nsetp.ne.b32 p, %66, 0;\nmov.b64 a, {%64, 0x40000040};\nmov.b64 b, {%65, 0x40000040};\n"
    "wgmma.mma_async.sync.aligned.m64n128k16.f32.bf16.bf16 {%0,%1,%2,%3,%4,%5,%6,%7,%8,%9,%10,%11,%12,%13,%14,%15,%16,%17,%18,%19,%20,%21,%22,%23,%24,%25,%26,%27,%28,%29,%30,%31,%32,%33,%34,%35,%36,%37,%38,%39,%40,%41,%42,%43,%44,%45,%46,%47,%48,%49,%50,%51,%52,%53,%54,%55,%56,%57,%58,%59,%60,%61,%62,%63}, a, b, p, 1, 1, 0, 1;\n}\n"
    : "+f"(d[64]),"+f"(d[65]),"+f"(d[66]),"+f"(d[67]),"+f"(d[68]),"+f"(d[69]),"+f"(d[70]),"+f"(d[71]),"+f"(d[72]),"+f"(d[73]),"+f"(d[74]),"+f"(d[75]),"+f"(d[76]),"+f"(d[77]),"+f"(d[78]),"+f"(d[79]),"+f"(d[80]),"+f"(d[81]),"+f"(d[82]),"+f"(d[83]),"+f"(d[84]),"+f"(d[85]),"+f"(d[86]),"+f"(d[87]),"+f"(d[88]),"+f"(d[89]),"+f"(d[90]),"+f"(d[91]),"+f"(d[92]),"+f"(d[93]),"+f"(d[94]),"+f"(d[95]),"+f"(d[96]),"+f"(d[97]),"+f"(d[98]),"+f"(d[99]),"+f"(d[100]),"+f"(d[101]),"+f"(d[102]),"+f"(d[103]),"+f"(d[104]),"+f"(d[105]),"+f"(d[106]),"+f"(d[107]),"+f"(d[108]),"+f"(d[109]),"+f"(d[110]),"+f"(d[111]),"+f"(d[112]),"+f"(d[113]),"+f"(d[114]),"+f"(d[115]),"+f"(d[116]),"+f"(d[117]),"+f"(d[118]),"+f"(d[119]),"+f"(d[120]),"+f"(d[121]),"+f"(d[122]),"+f"(d[123]),"+f"(d[124]),"+f"(d[125]),"+f"(d[126]),"+f"(d[127])
    : "r"(da), "r"(db), "r"(sd));
}
__device__ __forceinline__ void cmma(float (&d)[16], uint32_t a0, uint32_t a1, uint32_t a2, uint32_t a3, uint32_t db, int sd) {
  asm volatile("{\n.reg .pred p;\n.reg .b64 b;\nsetp.ne.b32 p, %21, 0;\nmov.b64 b, {%20, 8};\n"
    "wgmma.mma_async.sync.aligned.m64n32k16.f32.bf16.bf16 {%0,%1,%2,%3,%4,%5,%6,%7,%8,%9,%10,%11,%12,%13,%14,%15}, {%16,%17,%18,%19}, b, p, 1, 1, 0;\n}\n"
    : "+f"(d[0]),"+f"(d[1]),"+f"(d[2]),"+f"(d[3]),"+f"(d[4]),"+f"(d[5]),"+f"(d[6]),"+f"(d[7]),"+f"(d[8]),"+f"(d[9]),"+f"(d[10]),"+f"(d[11]),"+f"(d[12]),"+f"(d[13]),"+f"(d[14]),"+f"(d[15])
    : "r"(a0), "r"(a1), "r"(a2), "r"(a3), "r"(db), "r"(sd));
}

__device__ __forceinline__ void wg_fence() { asm volatile("wgmma.fence.sync.aligned;" ::: "memory"); }
__device__ __forceinline__ void wg_commit() { asm volatile("wgmma.commit_group.sync.aligned;" ::: "memory"); }
template <int N> __device__ __forceinline__ void wg_wait() { asm volatile("wgmma.wait_group.sync.aligned %0;" ::"n"(N) : "memory"); }
__device__ __forceinline__ uint32_t mkdesc(uint32_t addr, uint32_t lbo) { return ((addr & 0x3FFFF) >> 4) | ((lbo >> 4) << 16); }
__device__ __forceinline__ uint32_t smem_u32(const void* p) { return (uint32_t)__cvta_generic_to_shared(p); }
__device__ __forceinline__ void mbar_init(uint32_t bar, uint32_t cnt) { asm volatile("mbarrier.init.shared::cta.b64 [%0], %1;" ::"r"(bar), "r"(cnt) : "memory"); }
__device__ __forceinline__ void mbar_expect_tx(uint32_t bar, uint32_t bytes) { asm volatile("mbarrier.arrive.expect_tx.shared::cta.b64 _, [%0], %1;" ::"r"(bar), "r"(bytes) : "memory"); }
__device__ __forceinline__ void mbar_arrive(uint32_t bar) { asm volatile("mbarrier.arrive.shared::cta.b64 _, [%0];" ::"r"(bar) : "memory"); }
__device__ __forceinline__ uint32_t mapa(uint32_t a, uint32_t cta) { uint32_t r; asm volatile("mapa.shared::cluster.u32 %0, %1, %2;" : "=r"(r) : "r"(a), "r"(cta)); return r; }
__device__ __forceinline__ void mbar_arrive_remote(uint32_t rbar) { asm volatile("mbarrier.arrive.shared::cluster.b64 _, [%0];" ::"r"(rbar) : "memory"); }
__device__ __forceinline__ void mbar_arrive_remote4(uint32_t rbar) { asm volatile("mbarrier.arrive.shared::cluster.b64 _, [%0], 4;" ::"r"(rbar) : "memory"); }
__device__ __forceinline__ void mbar_wait(uint32_t bar, uint32_t parity) {
  asm volatile("{\n.reg .pred p;\n.reg .u32 n;\nmov.u32 n, 0;\nLW:\nmbarrier.try_wait.parity.shared::cta.b64 p, [%0], %1;\n@p bra LD;\n"
               "add.u32 n, n, 1;\nsetp.lt.u32 p, n, 4000000;\n@p bra LW;\ntrap;\nLD:\n}\n" ::"r"(bar), "r"(parity) : "memory");
}
__device__ __forceinline__ void tma2d(uint32_t dst, const CUtensorMap* m, uint32_t bar, int c0, int c1) {
  asm volatile("cp.async.bulk.tensor.2d.shared::cluster.global.mbarrier::complete_tx::bytes [%0], [%1, {%3, %4}], [%2];" ::"r"(dst), "l"(m), "r"(bar), "r"(c0), "r"(c1) : "memory");
}
__device__ __forceinline__ void tma3d_mc(uint32_t dst, const CUtensorMap* m, uint32_t bar, int c0, int c1, int c2, uint16_t mask) {
  asm volatile("cp.async.bulk.tensor.3d.shared::cluster.global.mbarrier::complete_tx::bytes.multicast::cluster [%0], [%1, {%3, %4, %5}], [%2], %6;" ::"r"(dst), "l"(m), "r"(bar), "r"(c0), "r"(c1), "r"(c2), "h"(mask) : "memory");
}
__device__ __forceinline__ void tma5d_mc(uint32_t dst, const CUtensorMap* m, uint32_t bar, int c0, int c4) {
  asm volatile("cp.async.bulk.tensor.5d.shared::cluster.global.mbarrier::complete_tx::bytes.multicast::cluster [%0], [%1, {%3, %5, %5, %5, %4}], [%2], %6;" ::"r"(dst), "l"(m), "r"(bar), "r"(c0), "r"(c4), "r"(0), "h"((uint16_t)3) : "memory");
}
__device__ __forceinline__ void tma2d_store(const CUtensorMap* m, uint32_t src, int c0, int c1) {
  asm volatile("cp.async.bulk.tensor.2d.global.shared::cta.bulk_group [%0, {%2, %3}], [%1];" ::"l"(m), "r"(src), "r"(c0), "r"(c1) : "memory");
}
__device__ __forceinline__ void bulk_g2s(uint32_t dst, const void* src, uint32_t bytes, uint32_t bar) {
  asm volatile("cp.async.bulk.shared::cluster.global.mbarrier::complete_tx::bytes [%0], [%1], %2, [%3];" ::"r"(dst), "l"(src), "r"(bytes), "r"(bar) : "memory");
}
__device__ __forceinline__ void fence_async() { asm volatile("fence.proxy.async.global;" ::: "memory"); }
__device__ __forceinline__ void bar_sync(int id, int n) { asm volatile("bar.sync %0, %1;" ::"r"(id), "r"(n) : "memory"); }
__device__ __forceinline__ void bar_arrive(int id, int n) { asm volatile("bar.arrive %0, %1;" ::"r"(id), "r"(n) : "memory"); }
__device__ __forceinline__ uint32_t lds32(uint32_t a) { uint32_t v; asm volatile("ld.volatile.shared.b32 %0, [%1];" : "=r"(v) : "r"(a)); return v; }
__device__ __forceinline__ void sts128(uint32_t a, float x, float y, float z, float w) { asm volatile("st.shared.v4.f32 [%0], {%1,%2,%3,%4};" ::"r"(a), "f"(x), "f"(y), "f"(z), "f"(w) : "memory"); }
__device__ __forceinline__ float4 lds128(uint32_t a) { float4 v; asm volatile("ld.shared.v4.f32 {%0,%1,%2,%3}, [%4];" : "=f"(v.x), "=f"(v.y), "=f"(v.z), "=f"(v.w) : "r"(a) : "memory"); return v; }
__device__ __forceinline__ void stg128(void* p, uint32_t a, uint32_t b, uint32_t c, uint32_t d) { asm volatile("st.global.v4.b32 [%0], {%1,%2,%3,%4};" ::"l"(p), "r"(a), "r"(b), "r"(c), "r"(d) : "memory"); }
__device__ __forceinline__ void sts128u(uint32_t a, uint32_t x, uint32_t y, uint32_t z, uint32_t w) { asm volatile("st.shared.v4.b32 [%0], {%1,%2,%3,%4};" ::"r"(a), "r"(x), "r"(y), "r"(z), "r"(w) : "memory"); }
__device__ __forceinline__ void signal(int c, unsigned inc) { asm volatile("red.release.gpu.global.add.u32 [%0], %1;" ::"l"(g_cnt + c * 32), "r"(inc) : "memory"); }
__device__ __forceinline__ unsigned ld_epoch() { unsigned v; asm volatile("ld.relaxed.gpu.global.u32 %0, [%1];" : "=r"(v) : "l"(g_cnt + C_TK * 32) : "memory"); return (v >> 7) + 1; }
constexpr int SPINMAX = 1000000;
__device__ __forceinline__ void spin_guard(int n) { asm volatile("{\n.reg .pred p;\nsetp.gt.s32 p, %0, 1000000;\n@p trap;\n}\n" ::"r"(n)); }
__device__ __forceinline__ void wait_cnt(int c, unsigned ep) {
  unsigned v, n = 0;
  while (true) {
    asm volatile("ld.acquire.gpu.global.u32 %0, [%1];" : "=r"(v) : "l"(g_cnt + c * 32) : "memory");
    if ((int)(v - (ep << 7)) >= 0) break;
    spin_guard(++n);
    __nanosleep(20);
  }
}
__device__ __forceinline__ uint4 ldg128_rlx(const void* p) { uint4 v; asm volatile("ld.relaxed.gpu.global.v4.b32 {%0,%1,%2,%3}, [%4];" : "=r"(v.x), "=r"(v.y), "=r"(v.z), "=r"(v.w) : "l"(p) : "memory"); return v; }
__device__ __forceinline__ uint2 ldg64_rlx(const void* p) { uint2 v; asm volatile("ld.relaxed.gpu.global.v2.b32 {%0,%1}, [%2];" : "=r"(v.x), "=r"(v.y) : "l"(p) : "memory"); return v; }
__device__ __forceinline__ void stg64_rlx(void* p, uint32_t a, uint32_t b) { asm volatile("st.relaxed.gpu.global.v2.b32 [%0], {%1,%2};" ::"l"(p), "r"(a), "r"(b) : "memory"); }
__device__ __forceinline__ void stg128_rlx(void* p, uint32_t a, uint32_t b, uint32_t c, uint32_t d) { asm volatile("st.relaxed.gpu.global.v4.b32 [%0], {%1,%2,%3,%4};" ::"l"(p), "r"(a), "r"(b), "r"(c), "r"(d) : "memory"); }
__device__ __forceinline__ uint32_t pack2(float lo, float hi) { uint32_t r; asm("cvt.rn.bf16x2.f32 %0, %1, %2;" : "=r"(r) : "f"(hi), "f"(lo)); return r; }
__device__ __forceinline__ float blo(uint32_t v) { return __uint_as_float(v << 16); }
__device__ __forceinline__ float bhi(uint32_t v) { return __uint_as_float(v & 0xffff0000u); }
__device__ __forceinline__ float rbf(float x) { return __bfloat162float(__float2bfloat16_rn(x)); }
__device__ __forceinline__ uint32_t hmul2(uint32_t a, uint32_t b) { uint32_t r; asm("mul.rn.bf16x2 %0, %1, %2;" : "=r"(r) : "r"(a), "r"(b)); return r; }
__device__ __forceinline__ uint32_t hadd2(uint32_t a, uint32_t b) { uint32_t r; asm("add.rn.bf16x2 %0, %1, %2;" : "=r"(r) : "r"(a), "r"(b)); return r; }
__device__ __forceinline__ uint32_t hfma2(uint32_t a, uint32_t b, uint32_t c) { uint32_t r; asm("fma.rn.bf16x2 %0, %1, %2, %3;" : "=r"(r) : "r"(a), "r"(b), "r"(c)); return r; }
__device__ __forceinline__ uint32_t ldg32(const void* p) { uint32_t v; asm volatile("ld.global.nc.b32 %0, [%1];" : "=r"(v) : "l"(p)); return v; }
__device__ __forceinline__ uint4 ldg128(const void* p) { uint4 v; asm volatile("ld.global.nc.v4.b32 {%0,%1,%2,%3}, [%4];" : "=r"(v.x), "=r"(v.y), "=r"(v.z), "=r"(v.w) : "l"(p)); return v; }
__device__ __forceinline__ uint2 ldg64(const void* p) { uint2 v; asm volatile("ld.global.nc.v2.b32 {%0,%1}, [%2];" : "=r"(v.x), "=r"(v.y) : "l"(p)); return v; }
__device__ __forceinline__ uint32_t ldg16(const void* p, int on) { uint32_t v; asm volatile("{\n.reg .pred p;\nsetp.ne.s32 p, %2, 0;\nmov.u32 %0, 0;\n@p ld.global.nc.u16 %0, [%1];\n}\n" : "=r"(v) : "l"(p), "r"(on)); return v; }
__device__ __forceinline__ void tma3d(uint32_t dst, const CUtensorMap* m, uint32_t bar, int c0, int c1) {
  asm volatile("cp.async.bulk.tensor.3d.shared::cluster.global.mbarrier::complete_tx::bytes [%0], [%1, {%3, %4, %5}], [%2];" ::"r"(dst), "l"(m), "r"(bar), "r"(c0), "r"(c1), "r"(0) : "memory");
}
__device__ __forceinline__ void ldsm4t(uint32_t* r, uint32_t a) { asm volatile("ldmatrix.sync.aligned.m8n8.x4.trans.shared.b16 {%0,%1,%2,%3}, [%4];" : "=r"(r[0]), "=r"(r[1]), "=r"(r[2]), "=r"(r[3]) : "r"(a) : "memory"); }
__device__ __forceinline__ uint32_t movm(uint32_t v) { uint32_t r; asm volatile("movmatrix.sync.aligned.m8n8.trans.b16 %0, %1;" : "=r"(r) : "r"(v)); return r; }
__device__ __forceinline__ float ex2(float x) { float r; asm("ex2.approx.ftz.f32 %0, %1;" : "=f"(r) : "f"(x)); return r; }
__device__ __forceinline__ float rcp(float x) { float r; asm("rcp.approx.ftz.f32 %0, %1;" : "=f"(r) : "f"(x)); return r; }
__device__ __forceinline__ float mish(float h) {
  float u = ex2(h * 1.4426950408889634f) + 1.f;
  return h * fmaf(rcp(fmaf(u, u, 1.f)), -2.f, 1.f);
}
__device__ __forceinline__ float silu(float z) { return z * rcp(1.f + ex2(z * -1.4426950408889634f)); }

__device__ __forceinline__ uint32_t cpy(uint32_t v, uint32_t z) { uint32_t r; asm volatile("xor.b32 %0, %1, %2;" : "=r"(r) : "r"(v), "r"(z)); return r; }
template <int HG> __device__ __forceinline__ void loadA(uint32_t (&x)[16], uint32_t hb) {
  uint32_t b = hb + (HG >> 1) * 1024 + (HG & 1) * 128;
  x[0] = lds32(b);
#pragma unroll
  for (int r = 0; r < 4; r++) { x[4 * r + 1] = lds32(b + (2 * r + 1) * 16); x[4 * r + 3] = lds32(b + (2 * r + 2) * 16); }
}
__device__ __forceinline__ void dupA(uint32_t (&x)[16], uint32_t z) {
#pragma unroll
  for (int r = 0; r < 4; r++) { x[4 * r + 2] = cpy(x[4 * r + 1], z); if (r < 3) x[4 * r + 4] = cpy(x[4 * r + 3], z); }
}
template <int HG> __device__ __forceinline__ void mmaG(float (&d)[4][16], uint32_t (&x)[16], uint32_t dbase) {
  wg_fence();
#pragma unroll
  for (int rr = 0; rr < 4; rr++) {
    constexpr int SP = HG >> 1;
    int r = (HG & 1) * 4 + rr;
    uint32_t db = dbase + (SP * 32 + r);
    int sd = (HG | rr) != 0;
#pragma unroll
    for (int c = 0; c < 4 - SP; c++) cmma(d[c], x[4 * rr], x[4 * rr + 1], x[4 * rr + 2], x[4 * rr + 3], db + 32 * c, sd);
  }
  wg_commit();
}

struct Params {
  const bf16 *x, *k, *v, *shk, *hk, *Dv, *b1, *w1;
  uint32_t zero;
};

__device__ __forceinline__ void act_chunk(const uint32_t* h, bf16* dst) {
  uint32_t o[4];
#pragma unroll
  for (int i = 0; i < 4; i++) o[i] = pack2(mish(blo(h[i])), mish(bhi(h[i])));
  stg128(dst, o[0], o[1], o[2], o[3]);
}

#define LOCALS const uint32_t tid = threadIdx.x; \
  const int lane = tid & 31, w = (tid >> 5) & 3, g = lane >> 2, q = lane & 3, wg = tid >> 7; (void)w; (void)g; (void)q; (void)wg

#define WGU __shfl_sync(0xffffffff, wg, 0)
enum { NB_ORD0 = 1, NB_ORD1 = 2, NB_WG0 = 3, NB_WG1 = 4, NB_CS = 5, NB_ACT = 6, NB_Y = 7, NB_U = 11, NB_ST = 12 };

__global__ void __cluster_dims__(2, 1, 1) __launch_bounds__(384, 1)
fused_kernel(const __grid_constant__ CUtensorMap m_x, const __grid_constant__ CUtensorMap m_w1, const __grid_constant__ CUtensorMap m_act,
             const __grid_constant__ CUtensorMap m_w2, const __grid_constant__ CUtensorMap m_y, const __grid_constant__ CUtensorMap m_out,
             const __grid_constant__ CUtensorMap m_k, const __grid_constant__ CUtensorMap m_v, const Params p) {
  extern __shared__ __align__(1024) uint8_t smem_raw[];
  const uint32_t sb = smem_u32(smem_raw);
  const uint32_t bfull = sb + SM_BARS, bempty = bfull + 32, bepi = bfull + 64, bxt = bfull + 72, byf = bfull + 80, bdep = bfull + 88, bkv = bfull + 136, bhl = bfull + 152, bh = bfull + 184, bkf = bfull + 216, s_par = bfull + 224;
  const uint32_t s_cb = sb + SM_CB, s_st = sb + SM_ST, s_xt = sb + SM_XT;
  const int cta = blockIdx.x, cid = cta >> 1, rank = cta & 1;
  const int mp = cid & 7, jn = cid >> 3;
  const int tm = mp * 2 + rank;
  const int tn2 = jn & 3, kh = jn >> 2;
  const int c0 = tn2 * 256 + kh * 128;
  if (threadIdx.x == 256) {
    asm volatile("prefetch.tensormap [%0];" ::"l"(&m_x) : "memory");
    asm volatile("prefetch.tensormap [%0];" ::"l"(&m_w1) : "memory");
    for (int s = 0; s < NST; s++) { mbar_init(bfull + s * 8, 1); mbar_init(bempty + s * 8, 16); mbar_init(bh + s * 8, 2); }
    mbar_init(bepi, 2); mbar_init(bxt, 1); mbar_init(byf, 8); mbar_init(bkf, 8);
    for (int s = 0; s < 12; s++) mbar_init(bdep + s * 8, 1);
    if (sb & 1023) asm volatile("trap;");
    asm volatile("fence.mbarrier_init.release.cluster;" ::: "memory");
    STAMP(0);
  }
  __syncwarp();
  asm volatile("barrier.cluster.arrive.relaxed.aligned;" ::: "memory");
  if (__shfl_sync(0xffffffff, threadIdx.x >> 7, 0) == 2) {
    asm volatile("setmaxnreg.dec.sync.aligned.u32 56;");
    const int warp = (threadIdx.x >> 5) & 3, lane = threadIdx.x & 31;
    if (threadIdx.x == 256) {
      mbar_expect_tx(bfull, 16384 + B1BYTES);
      tma2d(sb, &m_x, bfull, 2 * mp * 64, tm * 128);
    }
    __syncwarp();
    asm volatile("barrier.cluster.wait.aligned;" ::: "memory");
    if (warp == 0) {
      if (lane == 0) {
        uint32_t ph = 1;
        PSTAMP(1);
#pragma unroll 1
        for (int it = 0; it < 32; it++) {
          int st = it & 3, t = it >> 4, kb = (it + 2 * mp + 12 * t) & 15;
          uint32_t a = sb + st * STAGE, b = a + 16384;
          mbar_wait(bempty + st * 8, ph);
          const bool keep = (it >> 2) == 4;
          if (it) mbar_expect_tx(bfull + st * 8, keep ? B1BYTES : 16384 + B1BYTES);
          if (it && !keep) tma2d(a, &m_x, bfull + st * 8, kb * 64, tm * 128);
          tma3d_mc(b + rank * (B1BYTES / 2), &m_w1, bfull + st * 8, 0, kb * 64 + rank * 32, (jn + 8 * t) * 7, 3);
          if (it < 4) PSTAMP(112 + it);
          if (it == XPF) asm volatile("cp.async.bulk.prefetch.L2.global [%0], 32768;" ::"l"(p.x + (size_t)(tm * 128 + jn * 16) * D_) : "memory");
          if (it == HKPF) asm volatile("cp.async.bulk.prefetch.L2.global [%0], 32768;" ::"l"(p.hk + (size_t)cta * 8 * S_) : "memory");
          if (st == 3) ph ^= 1;
        }
        mbar_wait(bdep, 0);
        fence_async();
#pragma unroll 1
        for (int st = 0; st < 4; st++) {
          mbar_wait(bempty + st * 8, ph);
          mbar_expect_tx(bhl + st * 8, 8192);
          mbar_expect_tx(bfull + st * 8, 2 * UCH);
#pragma unroll 1
          for (int j = 0; j < 2; j++) {
            int ch = cta * 8 + st * 2 + j;
            uint32_t dst = sb + st * STAGE + j * CHB;
            bulk_g2s(dst + CH0, p.hk + (size_t)ch * S_, 4096, bhl + st * 8);
            bulk_g2s(dst + CU0, g_U + (size_t)ch * UCH, UARR, bfull + st * 8);
            bulk_g2s(dst + CU1, g_U + (size_t)ch * UCH + UARR, UARR, bfull + st * 8);
          }
        }
        ph ^= 1;
#pragma unroll 1
        for (int it = 0; it < 28; it++) {
          int st = it & 3;
          uint32_t a = sb + st * STAGE, b = a + 16384;
          int k0 = kh * 896 + (it < 14 ? it * 64 : 1792 + (int)((0xDA9632C851B740ull >> (4 * (it - 14))) & 15) * 64);
          if (it == 0 || it == 14 || it == 18 || it == 22) { PSTAMP(64 + (it >> 1)); mbar_wait(bdep + (it ? (it - 6) * 2 : 8), 0); fence_async(); PSTAMP(65 + (it >> 1)); }
          mbar_wait(bempty + st * 8, ph);
          mbar_expect_tx(bfull + st * 8, STAGE);
          tma2d(a, &m_act, bfull + st * 8, k0, tm * 128);
#pragma unroll 1
          for (int j = rank * 2; j < rank * 2 + 2; j++) tma5d_mc(b + j * 8192, &m_w2, bfull + st * 8, tn2 * 256 + ((j ^ (2 * (kh ^ 1))) * 64), k0 >> 5);
          if (it == 13) {
            mbar_wait(bdep + 40, 0);
            fence_async();
            mbar_expect_tx(bxt, 32768);
            tma2d(s_xt, &m_y, bxt, tm * 128, c0);
            tma2d(s_xt + 16384, &m_y, bxt, tm * 128 + 64, c0);
          }
          if (it == 19) {
            mbar_wait(byf, 1);
            mbar_expect_tx(bxt, 32768);
            tma2d(s_xt, &m_x, bxt, c0, tm * 128);
            tma2d(s_xt + 16384, &m_x, bxt, c0 + 64, tm * 128);
          }
          if (st == 3) ph ^= 1;
        }
      }
    } else if (warp == 1) {
      const unsigned par = ld_epoch() & 1;
#pragma unroll 1
      for (int t = 0; t < 2; t++) {
        const int col = (lane >> 2) * 14 + (lane & 3) * 4;
        uint32_t bb[4];
#pragma unroll
        for (int i = 0; i < 4; i++) bb[i] = ldg32(p.b1 + (jn + 8 * t) * 224 + min(col + (i >> 1) * 112 + (i & 1) * 2, 222));
        bar_sync(NB_CS, 288);
        if (t == 0) PSTAMP(24);
#pragma unroll 1
        for (int h = 0, n = 0; h < 2; n++) {
          const float* src = g_csp + (jn + 8 * t) * 256 + (lane + 32 * h) * 4;
          uint4 v[8];
          uint32_t bad = 0;
#pragma unroll
          for (int j = 0; j < 8; j++) v[j] = ldg128_rlx(src + j * 4096);
          float4 s = make_float4(0.f, 0.f, 0.f, 0.f);
#pragma unroll
          for (int j = 0; j < 8; j++) {
            bad |= (v[j].x ^ par) | (v[j].z ^ par);
            s.x += __uint_as_float(v[j].x); s.y += __uint_as_float(v[j].y); s.z += __uint_as_float(v[j].z); s.w += __uint_as_float(v[j].w);
          }
          if (!__any_sync(0xffffffff, bad & 1)) {
            sts128(s_cb + (col + h * 112) * 8, s.x, s.y, blo(bb[0]), bhi(bb[0]));
            if ((lane & 3) != 3) sts128(s_cb + (col + h * 112) * 8 + 16, s.z, s.w, blo(bb[1]), bhi(bb[1]));
            bb[0] = bb[2]; bb[1] = bb[3];
            h++;
          }
          spin_guard(n);
        }
        __syncwarp();
        if (lane <= t) mbar_arrive(bepi);
        PSTAMP(25 + t);
      }
#pragma unroll 1
      for (int i = 0; i < 5; i++) {
        bar_sync(NB_ACT + i, 288);
        PSTAMP(80 + 2 * i);
        if (lane == 0) {
          if (i == 1) signal(C_Y + (cta >> 4), 8);
          else signal(C_ACT + (tm * 2 + kh) * 4 + (i ? i - 1 : 0), 32);
        }
        PSTAMP(81 + 2 * i);
        __syncwarp();
      }
      if (lane == 0) asm volatile("red.relaxed.gpu.global.add.u32 [%0], 1;" ::"l"(g_cnt + C_TK * 32) : "memory");
    } else {
      const unsigned ep = ld_epoch();
      const int u_ = warp - 2;
      if (u_ == 0) {
        auto ldkv = [&](int i) {
          const uint32_t bb = bkv + (i & 1) * 8, buf = s_xt + (i & 1) * 16384;
          mbar_expect_tx(bb, 16384);
          tma3d(buf, &m_k, bb, (cta & 15) * 64, (cta >> 4) * 16 + i * 4);
          tma3d(buf + 8192, &m_v, bb, (cta & 15) * 64, (cta >> 4) * 16 + i * 4);
        };
#pragma unroll 1
        for (int i = 0; i <= UWAIT + UW2; i++) {
          mbar_wait(bfull + (i & 3) * 8, (i >> 2) & 1);
          if ((i == UWAIT || i == UWAIT + UW2) && lane == 0) ldkv(i != UWAIT);
          if (i >= KVK && i < KVK + 4) {
            const size_t o = (size_t)((cta >> 4) * 256 + 128 + (i - KVK) * 32 + lane) * D_ + (cta & 15) * 64;
            asm volatile("prefetch.global.L2 [%0];" ::"l"(p.k + o) : "memory");
            asm volatile("prefetch.global.L2 [%0];" ::"l"(p.v + o) : "memory");
          }
          if (i >= W1K && i < W1K + 2) {
            const bf16* wp = p.w1 + (size_t)(((i - W1K + 2 * mp) & 15) * 64 + rank * 32 + lane) * F_ + (jn + 8) * 224;
#pragma unroll
            for (int c = 0; c < 4; c++) asm volatile("prefetch.global.L2 [%0];" ::"l"(wp + c * 64) : "memory");
          }
        }
        if (lane == 0) {
#pragma unroll 1
          for (int i = 2; i < 4; i++) { mbar_wait(i == 2 ? bkf : byf, 0); ldkv(i); }
        }
        __syncwarp();
        bar_sync(NB_U, 288);
        if (lane == 0) {
          PSTAMP(32);
          signal(C_U + (cta & 15), 16);
          PSTAMP(30);
          wait_cnt(C_U + (cta >> 3), ep);
          mbar_arrive(bdep);
        }
      } else {
        bar_sync(NB_ST, 288);
        uint2 v[4];
#pragma unroll 1
        for (int n = 0;; n++) {
          uint32_t bad = 0;
#pragma unroll
          for (int j = 0; j < 4; j++) v[j] = ldg64_rlx(g_stat + tm * 128 + (lane >> 3) * 16 + (lane & 7) + (j >> 1) * 64 + (j & 1) * 8);
#pragma unroll
          for (int j = 0; j < 4; j++) bad |= v[j].x ^ ep;
          if (!__any_sync(0xffffffff, bad & 0xffff)) break;
          spin_guard(n);
        }
#pragma unroll
        for (int j = 0; j < 4; j += 2) sts128u(s_st + lane * 16 + j * 256, (v[j].x & 0xffff0000u) ^ 0x80000000u, v[j].y, (v[j + 1].x & 0xffff0000u) ^ 0x80000000u, v[j + 1].y);
        __syncwarp();
        if (lane == 0) mbar_arrive(bepi);
        PSTAMP(27);
      }
      __syncwarp();
      const uint32_t dv = ldg16(p.Dv + cta * 8 + (lane & 3) * 2 + u_, 1) << 16;
#pragma unroll 1
      for (int i = 0; i < 8; i++) {
        const uint32_t hs = sb + (i >> 1) * STAGE + u_ * CHB + CH0 + (i & 1) * 2048 + lane * 16;
        if (!(i & 1)) mbar_wait(bhl + (i >> 1) * 8, 0);
        float4 v[4];
        uint32_t pv[4];
#pragma unroll
        for (int j = 0; j < 4; j++) { v[j] = lds128(hs + j * 512); pv[j] = lds32(hs + j * 512 - 4); }
        if (!((i & 1) | lane)) pv[0] = 0;
#pragma unroll
        for (int j = 0; j < 4; j++) {
          const uint32_t x = __float_as_uint(v[j].x), y = __float_as_uint(v[j].y), z = __float_as_uint(v[j].z), w = __float_as_uint(v[j].w);
          sts128u(hs + (CH1 - CH0) + j * 512, __byte_perm(pv[j], x, 0x5432), __byte_perm(x, y, 0x5432), __byte_perm(y, z, 0x5432), __byte_perm(z, w, 0x5432));
        }
        if (lane * 2 == i) asm volatile("st.shared.b32 [%0], %1;" ::"r"(sb + lane * STAGE + u_ * CHB), "r"(dv) : "memory");
        if (i & 1) { __syncwarp(); if (lane == 0) mbar_arrive(bh + (i >> 1) * 8); }
      }
      if (lane == 0) {
        if (u_ == 0) {
#pragma unroll 1
          for (int i = 0; i < 4; i++) { wait_cnt(C_ACT + (tm * 2 + kh) * 4 + i, ep); mbar_arrive(bdep + 8 + i * 8); }
        } else {
          wait_cnt(C_Y + (c0 >> 7), ep);
          mbar_arrive(bdep + 40);
        }
      }
    }
  } else {
    asm volatile("setmaxnreg.inc.sync.aligned.u32 224;");
    const uint32_t e0 = mapa(bempty, 0), e1 = mapa(bempty, 1);
    uint32_t hp[56];
    asm volatile("barrier.cluster.wait.aligned;" ::: "memory");
    {
      float d[112];
#pragma unroll 1
      for (uint32_t t = 0; t < 2; t++) {
      LOCALS;
      uint2 sw = make_uint2(0, 0);
      uint32_t c0_ = 0, c1_ = 0;
      const uint32_t da0 = mkdesc(sb, 16) + WGU * 512, db0 = mkdesc(sb + 16384, 2048);
      auto kissue = [&](uint32_t kb) {
        const uint32_t st = kb & 3, so = st * (STAGE >> 4);
        mbar_wait(bfull + st * 8, (kb >> 2) & 1);
        wg_fence();
#pragma unroll
        for (int kk = 0; kk < 4; kk++) mma_n224(d, da0 + (so + kk * 2), db0 + (so + (((kk & 1) * 1024 + (kk >> 1) * (B1BYTES / 2)) >> 4)), kk || kb);
        wg_commit();
      };
      auto kretire = [&](uint32_t kb) {
        wg_wait<1>();
        if (kb && lane == 0) { mbar_arrive_remote(e0 + ((kb - 1) & 3) * 8); mbar_arrive_remote(e1 + ((kb - 1) & 3) * 8); }
      };
      auto kstep = [&](uint32_t kb) { kissue(kb); kretire(kb); };
      const int W = rank * 56 + (wg * 4 + w) * 7 + min(lane & 7, 6), hf = lane >> 4;
      const uint32_t csb = sb + 16384 + hf * (B1BYTES / 2) + (W >> 4) * 2048 + ((lane >> 3) & 1) * 64 + (W & 3) * 4;
      auto cs_ld = [&](uint32_t kb, int r) { return lds32(csb + kb * STAGE + (r & 12) * 128 + (((r ^ (hf * 2)) & 3) * 128 + ((((W >> 2) ^ r ^ (hf * 2)) & 3) << 4))); };
      auto cs_pub = [&](float cs0, float cs1, int t, uint32_t par) {
        cs0 += __shfl_xor_sync(0xffffffff, cs0, 8); cs1 += __shfl_xor_sync(0xffffffff, cs1, 8);
        cs0 += __shfl_xor_sync(0xffffffff, cs0, 16); cs1 += __shfl_xor_sync(0xffffffff, cs1, 16);
        if (lane < 8) stg64_rlx(g_csp + mp * 4096 + (jn + 8 * t) * 256 + (rank * 8 + wg * 4 + w) * 16 + lane * 2, (__float_as_uint(cs0) & ~1u) | par, __float_as_uint(cs1));
        bar_arrive(NB_CS, 288);
      };
      const int uch = (cta & 15) * 64 + (wg * 4 + w) * 8 + g, uT = (cta >> 4) * 256;
      const int rs_ = 4 * ((lane & 1) ^ 1) + 3 - ((lane >> 1) & 3);
      const uint32_t ma = s_xt + ((lane >> 3) * 8 + rs_) * 128 + ((rs_ ^ (wg * 4 + w)) << 4);
      uint8_t* ub = g_U + (size_t)uch * UCH + (124 - (uT >> 4) + q) * 16;
      auto ustep = [&](uint32_t i, auto&& mid) {
        uint32_t Q[10], V[8];
        const uint32_t la = ma + (i & 1) * 16384;
        mbar_wait(bkv + (i & 1) * 8, i >> 1);
        ldsm4t(Q + 6, la + 4096); ldsm4t(Q + 2, la); ldsm4t(V, la + 8192); ldsm4t(V + 4, la + 12288);
        mid();
        const uint32_t n0 = __shfl_sync(0xffffffff, Q[8], (lane & 28) | ((lane + 1) & 3)), n1 = __shfl_sync(0xffffffff, Q[9], (lane & 28) | ((lane + 1) & 3));
        asm volatile("" ::"r"(Q[2]), "r"(V[0]), "r"(V[4]) : "memory");
        __syncwarp();
        if (lane == 0 && i < 2) mbar_arrive(i ? byf : bkf);
        const uint32_t w0 = __byte_perm(sw.x, 0, 0x1010), w1 = __byte_perm(sw.x, 0, 0x3232), w2 = __byte_perm(sw.y, 0, 0x1010), w3 = __byte_perm(sw.y, 0, 0x3232);
        Q[0] = q == 3 ? c0_ : n0; Q[1] = q == 3 ? c1_ : n1;
        c0_ = n0; c1_ = n1;
        uint32_t pm = __byte_perm(Q[9], Q[8], 0x5432);
#pragma unroll
        for (int j = 7; j >= 0; j--) {
          const uint32_t pc = __byte_perm(Q[j + 1], Q[j], 0x5432);
          V[j] = hmul2(hfma2(Q[j + 2], w0, hfma2(pm, w1, hfma2(Q[j + 1], w2, hmul2(pc, w3)))), V[j]);
          pm = pc;
          if (j == 4) stg128(ub - i * 64, V[7], V[6], V[5], V[4]);
        }
        stg128(ub + UARR - i * 64, V[3], V[2], V[1], V[0]);
      };
        if (t == 0) {
          uint32_t c2_, lt = tid;
          asm volatile("" : "+r"(lt));
          const unsigned ep = ld_epoch();
          {
            const int srow = tm * 128 + jn * 16 + (lt >> 4);
            const uint4* xp = (const uint4*)(p.x + (size_t)srow * D_) + (lt & 15);
            uint4 xv[8];
            float f[64], a[4] = {0.f, 0.f, 0.f, 0.f}, cs0 = 0.f, cs1 = 0.f;
#pragma unroll
            for (int kb = 0; kb < 2; kb++) {
              uint32_t v[16];
              mbar_wait(bfull + kb * 8, 0);
#pragma unroll
              for (int r = 0; r < 16; r++) v[r] = cs_ld(kb, r);
              kstep(kb);
              if (kb == 0) STAMP(4 + wg);
              if (kb == 1) STAMP0(96);
#pragma unroll
              for (int i = 4 * kb; i < 4 * kb + 4; i++) xv[i] = ldg128(xp + i * 16);
#pragma unroll
              for (int r = 0; r < 16; r++) { cs0 += blo(v[r]); cs1 += bhi(v[r]); }
              asm volatile("" : "+f"(cs0), "+f"(cs1));
            }
            kstep(2);
            STAMP0(97);
            cs_pub(cs0, cs1, 0, ep & 1);
            asm volatile("st.shared.b32 [%0], %1;" ::"r"(s_par), "r"(ep & 1) : "memory");
            *(uint2*)(g_U + (size_t)((cta & 15) * 64 + (cta >> 4) * 8) * UCH + (lt >> 4) * UARR + 2048 + (lt & 15) * 8) = make_uint2(0, 0);
#pragma unroll
            for (int h = 0; h < 2; h++) {
              kstep(3 + h);
              STAMP0(98 + h);
#pragma unroll
              for (int i = 4 * h; i < 4 * h + 4; i++) {
                asm volatile("" : "+r"(xv[i].x), "+r"(xv[i].y), "+r"(xv[i].z), "+r"(xv[i].w));
                const uint32_t e[4] = {xv[i].x, xv[i].y, xv[i].z, xv[i].w};
#pragma unroll
                for (int c = 0; c < 4; c++) { f[8 * i + 2 * c] = blo(e[c]); f[8 * i + 2 * c + 1] = bhi(e[c]); a[c] += f[8 * i + 2 * c] + f[8 * i + 2 * c + 1]; }
              }
              asm volatile("" : "+f"(a[0]), "+f"(a[1]), "+f"(a[2]), "+f"(a[3]));
            }
            kstep(5);
            STAMP0(100);
            float m = (a[0] + a[1]) + (a[2] + a[3]);
#pragma unroll
            for (int o = 1; o < 16; o *= 2) m += __shfl_xor_sync(0xffffffff, m, o);
            m *= 1.f / D_;
            asm volatile("" : "+f"(m));
            {
              const int lch = (cta & 15) * 64 + (lt >> 2);
              const bf16* kp = p.k + (size_t)uT * D_ + lch;
              sw = ldg64(p.shk + lch * 4);
              c0_ = ldg16(kp - 3 * D_, uT); c1_ = ldg16(kp - D_, uT); c2_ = ldg16(kp - 2 * D_, uT);
            }
            kstep(6);
            STAMP0(101);
            asm volatile("" : "+f"(m));
            a[0] = a[1] = a[2] = a[3] = 0.f;
#pragma unroll
            for (int i = 0; i < 64; i++) { float c = f[i] - m; a[i & 3] = fmaf(c, c, a[i & 3]); }
            float var = (a[0] + a[1]) + (a[2] + a[3]), sq;
            asm volatile("" : "+f"(var));
            kstep(7);
            STAMP0(102);
#pragma unroll
            for (int o = 1; o < 16; o *= 2) var += __shfl_xor_sync(0xffffffff, var, o);
            asm("sqrt.approx.ftz.f32 %0, %1;" : "=f"(sq) : "f"(rbf(rbf(var * (1.f / D_)) + 1e-5f)));
            if (!(lane & 15)) stg128_rlx(g_stat + srow, __float_as_uint(rbf(m)) | (ep & 0xffff), __float_as_uint(rcp(rbf(sq))), 0, 0);
            bar_arrive(NB_ST, 288);
          }
#pragma unroll 1
          for (uint32_t kb = 8, i = 0; kb < 16; kb++) {
            if ((UMASK >> kb) & 1) {
              if (i == 0) { asm volatile("" : "+r"(c2_)); c1_ |= c2_ << 16; }
              ustep(i, [&]() { kstep(kb); });
              i++;
            } else kstep(kb);
            STAMP0(95 + kb);
          }
          bar_arrive(NB_U, 288);
        } else {
          float cs0 = 0.f, cs1 = 0.f;
#pragma unroll 1
          for (uint32_t kb = 0; kb < 2; kb++) {
            uint32_t v[16];
            mbar_wait(bfull + kb * 8, 0);
#pragma unroll
            for (int r = 0; r < 16; r++) v[r] = cs_ld(kb, r);
            kstep(kb);
#pragma unroll
            for (int r = 0; r < 16; r++) { cs0 += blo(v[r]); cs1 += bhi(v[r]); }
            STAMP0(90 + kb);
          }
          cs_pub(cs0, cs1, 1, lds32(s_par));
          bf16 *pa = g_act + (size_t)(tm * 128 + wg * 64 + w * 16 + g) * F_ + jn * 224 + q * 8, *pb = pa + 8 * F_;
#pragma unroll 1
          for (uint32_t i = 0; i < 2; i++) {
#pragma unroll
            for (int s = 0; s < 7; s++) {
              kstep(2 + i * 7 + s);
              act_chunk(hp + 4 * s, ((s & 1) ? pb : pa) + (s >> 1) * 32);
            }
#pragma unroll
            for (int s = 0; s < 28; s++) hp[s] = hp[s + 28];
            bf16* tp = pa; pa = pb + 96; pb = tp + 128;
          }
          bar_arrive(NB_ACT, 288);
        }
        wg_wait<0>();
        if (lane == 0) { mbar_arrive_remote(e0 + 24); mbar_arrive_remote(e1 + 24); }
        STAMP(6 + 4 * t + wg);
        mbar_wait(bepi, t);
        {
        LOCALS;
        const float4 st = lds128(s_st + (wg * 32 + w * 8 + g) * 16);
        const float nm0 = st.x, rs0 = st.y, nm1 = st.z, rs1 = st.w;
#pragma unroll
        for (int j = 0; j < 28; j++) {
          float4 cb = lds128(s_cb + j * 64 + q * 16);
          hp[(j >> 2) * 8 + (j & 3)] = pack2(fmaf(fmaf(nm0, cb.x, d[4 * j]), rs0, cb.z), fmaf(fmaf(nm0, cb.y, d[4 * j + 1]), rs0, cb.w));
          hp[(j >> 2) * 8 + 4 + (j & 3)] = pack2(fmaf(fmaf(nm1, cb.x, d[4 * j + 2]), rs1, cb.z), fmaf(fmaf(nm1, cb.y, d[4 * j + 3]), rs1, cb.w));
        }
        STAMP(8 + 4 * t + wg);
        }
      }
    }
    {
      LOCALS;
      const bool leader = (tid & 127) == 0;
      float d[4][16];
      uint32_t xa[16], xb[16], xc[16];
      uint32_t xoff[3], xok = 0;
      const uint32_t uoff = ((g & 1) ? CU0 : CU1) + (120 - 8 * w + 2 * (g >> 1)) * 16 + 12 - 4 * q;
      const uint32_t hoff = ((g & 1) ? CH0 : CH1) + (64 * w + (g >> 1) + q - 7) * 4;
      const int wu = WGU;
      const uint32_t zr = p.zero, dbs0 = mkdesc(sb + CU0, CU1 - CU0) + wu * (CHB >> 4);
      const uint32_t xbuf = sb + (2 + wg) * STAGE + XOFF + lane * 16;
#pragma unroll
      for (int dw = 1; dw < 4; dw++) {
        int w2 = (w + dw) & 3, i2 = 15 + w2 - w;
        if (i2 <= 15) xok |= 1u << dw;
        xoff[dw - 1] = xbuf + (w2 * 11 - (w2 * (w2 - 1)) / 2 + (i2 >> 2) * 3 + (i2 & 3)) * 512;
      }
      const uint32_t xb_w = xbuf + (w * 11 - (w * (w - 1)) / 2) * 512;
      if (wu == 1) bar_arrive(NB_ORD0, 256);
#pragma unroll 1
      for (int it = 0; it < 4; it++) {
        int ch = cta * 8 + it * 2 + wg;
        uint32_t ub = sb + it * STAGE + wg * CHB, hb = ub + hoff;
        const uint32_t dbs = dbs0 + it * (STAGE >> 4);
        mbar_wait(bfull + it * 8, 0);
        mbar_wait(bh + it * 8, 0);
        loadA<0>(xa, hb); loadA<1>(xb, hb); loadA<2>(xc, hb);
        dupA(xa, zr); dupA(xb, zr); dupA(xc, zr);
        if (it == 1) STAMP(58 + wg);
        bar_sync(NB_ORD0 + wu, 256);
        if (it == 1) STAMP(60 + wg);
        mmaG<0>(d, xa, dbs);
        mmaG<1>(d, xb, dbs);
        wg_wait<1>(); loadA<3>(xa, hb); mmaG<2>(d, xc, dbs); dupA(xa, zr);
        wg_wait<1>(); loadA<4>(xb, hb); mmaG<3>(d, xa, dbs); dupA(xb, zr);
        wg_wait<1>(); loadA<5>(xc, hb); mmaG<4>(d, xb, dbs); dupA(xc, zr);
        wg_wait<1>(); loadA<6>(xa, hb); mmaG<5>(d, xc, dbs); dupA(xa, zr);
        wg_wait<1>(); loadA<7>(xb, hb); mmaG<6>(d, xa, dbs); dupA(xb, zr);
        mmaG<7>(d, xb, dbs);
        if (!(it == 3 && wu == 1)) bar_arrive(NB_ORD0 + (wu ^ 1), 256);
        if (it == 0) STAMP(38 + wg);
        if (it == 1) STAMP(62 + wg);
        wg_wait<1>();
        uint32_t uu[8];
#pragma unroll
        for (int a = 0; a < 4; a++)
#pragma unroll
          for (int hh = 0; hh < 2; hh++) uu[2 * a + hh] = lds32(ub + uoff - a * 512 + hh * 16);
        const float dval = __uint_as_float(lds32(ub));
        wg_wait<0>();
        asm volatile("" ::"f"(dval), "r"(uu[0]), "r"(uu[1]), "r"(uu[2]), "r"(uu[3]), "r"(uu[4]), "r"(uu[5]), "r"(uu[6]), "r"(uu[7]) : "memory");
        if (it == 0) mbar_wait(bfull + (2 + wu) * 8, 0);
        bar_sync(NB_WG0 + wu, 128);
        if (leader && it != 2 + wg) { mbar_arrive_remote4(e0 + it * 8); mbar_arrive_remote4(e1 + it * 8); }
#pragma unroll
        for (int i = 0; i < 16; i++)
          if ((i & 3) != 3) {
            if (i >= 3 || i >= w) sts128(xb_w + ((i >> 2) * 3 + (i & 3)) * 512, d[i >> 2][4 * (i & 3)], d[i >> 2][4 * (i & 3) + 1], d[i >> 2][4 * (i & 3) + 2], d[i >> 2][4 * (i & 3) + 3]);
          }
        bar_sync(NB_WG0 + wu, 128);
        bf16* yp = g_Y + (size_t)ch * S_ + 128 * w + 112 - 32 * (g >> 1) + 8 * (g & 1) + 2 * q;
#pragma unroll
        for (int a = 0; a < 4; a++) {
          float s0 = d[3 - a][12], s1 = d[3 - a][13], s2 = d[3 - a][14], s3 = d[3 - a][15];
#pragma unroll
          for (int dw = 1; dw < 4; dw++)
            if (a > 0 || (xok >> dw) & 1) { float4 t = lds128(xoff[dw - 1] - a * 3 * 512); s0 += t.x; s1 += t.y; s2 += t.z; s3 += t.w; }
#pragma unroll
          for (int hh = 0; hh < 2; hh++) {
            uint32_t u2 = uu[2 * a + hh];
            float y0 = hh ? s1 : s0, y1 = hh ? s3 : s2;
            *(uint32_t*)(yp + 512 * a - 16 * hh) = hadd2(movm(pack2(y0, y1)), pack2(bhi(u2) * dval, blo(u2) * dval));
          }
        }
      }
      bar_arrive(NB_Y, 288);
      bar_sync(NB_WG0 + wu, 128);
      if (leader) { mbar_arrive_remote4(e0 + (2 + wg) * 8); mbar_arrive_remote4(e1 + (2 + wg) * 8); }
    }
    {
      LOCALS;
      STAMP(14 + wg);
      float d[128];
      const uint32_t da0 = mkdesc(sb, 16) + WGU * 512, db0 = mkdesc(sb + 16384, 8192);
      auto kstep = [&](uint32_t kb) {
        const uint32_t st = kb & 3, so = st * (STAGE >> 4);
        mbar_wait(bfull + st * 8, ((kb >> 2) & 1) ^ 1);
        wg_fence();
#pragma unroll
        for (int kk = 0; kk < 4; kk++) mma_n256(d, da0 + (so + kk * 2), db0 + (so + kk * 128), kk || kb);
        wg_commit();
        wg_wait<1>();
        if (kb && lane == 0) { mbar_arrive_remote(e0 + ((kb - 1) & 3) * 8); mbar_arrive_remote(e1 + ((kb - 1) & 3) * 8); }
      };
      {
        bf16 *pa = g_act + (size_t)(tm * 128 + wg * 64 + w * 16 + g) * F_ + (jn + 8) * 224 + q * 8, *pb = pa + 8 * F_;
#pragma unroll 1
        for (uint32_t i = 0; i < 2; i++) {
#pragma unroll
          for (int s = 0; s < 7; s++) {
            kstep(i * 7 + s);
            act_chunk(hp + 4 * s, ((s & 1) ? pb : pa) + (s >> 1) * 32);
            if (s == 5 && i == 0) bar_arrive(NB_ACT + 2, 288);
            if (s == 2 && i == 1) bar_arrive(NB_ACT + 3, 288);
          }
#pragma unroll
          for (int s = 0; s < 28; s++) hp[s] = hp[s + 28];
          bf16* tp = pa; pa = pb + 96; pb = tp + 128;
          STAMP(40 + 2 * i + wg);
        }
        bar_arrive(NB_ACT + 4, 288);
      }
      const int mr = lane & 7, mi = lane >> 3;
      uint32_t sr[32];
      kstep(14);
      mbar_wait(bxt, 0);
#pragma unroll
      for (int jp = 0; jp < 8; jp++) {
        uint32_t ya = s_xt + wg * 16384 + (jp * 16 + (mi >> 1) * 8 + mr) * 128 + (((w * 2 + (mi & 1)) ^ mr) << 4);
        asm volatile("ldmatrix.sync.aligned.m8n8.x4.trans.shared.b16 {%0,%1,%2,%3}, [%4];" : "=r"(sr[4 * jp]), "=r"(sr[4 * jp + 1]), "=r"(sr[4 * jp + 2]), "=r"(sr[4 * jp + 3]) : "r"(ya) : "memory");
      }
#pragma unroll 1
      for (uint32_t kb = 15; kb < 20; kb++) {
        kstep(kb);
        if (kb == 15) { asm volatile("" ::"r"(sr[3]), "r"(sr[7]), "r"(sr[11]), "r"(sr[15]), "r"(sr[19]), "r"(sr[23]), "r"(sr[27]), "r"(sr[31]) : "memory"); __syncwarp(); if (lane == 0) mbar_arrive(byf); }
      }
      STAMP(44 + wg);
      const uint32_t xrow = s_xt + (wg * 64 + w * 16 + (mi & 1) * 8 + mr) * 128;
      {
        const float4 st = lds128(s_st + (wg * 32 + w * 8 + g) * 16);
        const uint32_t nm[2] = {pack2(st.x, st.x), pack2(st.z, st.z)};
        const float rs[2] = {st.y, st.w};
        mbar_wait(bxt, 1);
#pragma unroll
        for (int jp = 0; jp < 8; jp++) {
          if (!(jp & 1)) kstep(20 + (jp >> 1));
          uint32_t xr[4], xa = xrow + (jp >> 2) * 16384 + ((((jp & 3) * 2 + (mi >> 1)) ^ mr) << 4);
          asm volatile("ldmatrix.sync.aligned.m8n8.x4.shared.b16 {%0,%1,%2,%3}, [%4];" : "=r"(xr[0]), "=r"(xr[1]), "=r"(xr[2]), "=r"(xr[3]) : "r"(xa) : "memory");
#pragma unroll
          for (int m = 0; m < 4; m++) {
            uint32_t xc = hadd2(xr[m], nm[m & 1]);
            sr[4 * jp + m] = hmul2(pack2(blo(xc) * rs[m & 1], bhi(xc) * rs[m & 1]), sr[4 * jp + m]);
          }
        }
      }
      kstep(24);
      const uint32_t par = lds32(s_par);
      STAMP(46 + wg);
#pragma unroll 1
      for (uint32_t st = 1; st < 4; st++) {
        const uint32_t so = st * (STAGE >> 4);
        mbar_wait(bfull + st * 8, 1);
        wg_fence();
#pragma unroll
        for (int kk = 0; kk < 4; kk++) mma_n256(d, da0 + (so + kk * 2), db0 + (so + kk * 128), 1);
        wg_commit();
      }
      wg_wait<0>();
      STAMP(16 + wg);
      {
        uint4* dst = g_xch + cta * 2048 + tid;
#pragma unroll
        for (int j = 0; j < 8; j++)
          stg128_rlx(dst + j * 256, (pack2(d[8 * j], d[8 * j + 1]) & ~1u) | par, pack2(d[8 * j + 2], d[8 * j + 3]), pack2(d[8 * j + 4], d[8 * j + 5]), pack2(d[8 * j + 6], d[8 * j + 7]));
      }
      STAMP(22 + wg);
      uint4 r[8];
      {
        const uint4* src = g_xch + (cta ^ PARTX) * 2048 + tid;
#pragma unroll 1
        for (int n = 0; n < SPINMAX; n++) {
          r[0] = ldg128_rlx(src + POLLJ * 256);
          if (!__any_sync(0xffffffff, (r[0].x ^ par) & 1)) break;
          __nanosleep(POLLNS);
        }
        STAMP(48 + wg);
#pragma unroll 1
        for (int n = 0; n < SPINMAX; n++) {
          uint32_t bad = 0;
#pragma unroll
          for (int j = 0; j < 8; j++) r[j] = ldg128_rlx(src + j * 256);
#pragma unroll
          for (int j = 0; j < 8; j++) bad |= r[j].x ^ par;
          if (!__any_sync(0xffffffff, bad & 1)) break;
        }
      }
      STAMP(50 + wg);
      wg_wait<0>();
      STAMP(18 + wg);
#pragma unroll
      for (int jp = 0; jp < 8; jp++) {
        uint32_t o[4], xr[4], xa = xrow + (jp >> 2) * 16384 + ((((jp & 3) * 2 + (mi >> 1)) ^ mr) << 4);
        asm volatile("ldmatrix.sync.aligned.m8n8.x4.shared.b16 {%0,%1,%2,%3}, [%4];" : "=r"(xr[0]), "=r"(xr[1]), "=r"(xr[2]), "=r"(xr[3]) : "r"(xa) : "memory");
#pragma unroll
        for (int c = 0; c < 2; c++) {
          int j = jp * 2 + c;
          const uint32_t ra = c ? r[jp].z : r[jp].x, rb = c ? r[jp].w : r[jp].y;
          float z[4] = {d[64 + 4 * j] + blo(ra), d[64 + 4 * j + 1] + bhi(ra), d[64 + 4 * j + 2] + blo(rb), d[64 + 4 * j + 3] + bhi(rb)};
#pragma unroll
          for (int hh = 0; hh < 2; hh++) {
            int m = c * 2 + hh;
            o[m] = hfma2(sr[4 * jp + m], pack2(silu(z[2 * hh]), silu(z[2 * hh + 1])), xr[m]);
          }
        }
        asm volatile("stmatrix.sync.aligned.m8n8.x4.shared.b16 [%0], {%1,%2,%3,%4};" ::"r"(xa), "r"(o[0]), "r"(o[1]), "r"(o[2]), "r"(o[3]) : "memory");
        if (jp == 3 || jp == 7) {
          asm volatile("fence.proxy.async.shared::cta;" ::: "memory");
          __syncwarp();
          if (lane == 0) {
            tma2d_store(&m_out, s_xt + (jp >> 2) * 16384 + (wg * 64 + w * 16) * 128, c0 + (jp >> 2) * 64, tm * 128 + wg * 64 + w * 16);
            asm volatile("cp.async.bulk.commit_group;" ::: "memory");
          }
        }
      }
      if (lane == 0) asm volatile("cp.async.bulk.wait_group.read 0;" ::: "memory");
      STAMP(20 + wg);
    }
  }
}

typedef CUresult (*EncFn)(CUtensorMap*, CUtensorMapDataType, cuuint32_t, void*, const cuuint64_t*, const cuuint64_t*, const cuuint32_t*, const cuuint32_t*,
                          CUtensorMapInterleave, CUtensorMapSwizzle, CUtensorMapL2promotion, CUtensorMapFloatOOBfill);
static CUtensorMap mkmap(EncFn enc, const void* ptr, int rank, const uint64_t* dims, const uint64_t* strides, const uint32_t* box, CUtensorMapSwizzle sw) {
  CUtensorMap m;
  uint32_t es[5] = {1, 1, 1, 1, 1};
  enc(&m, CU_TENSOR_MAP_DATA_TYPE_BFLOAT16, rank, (void*)ptr, (const cuuint64_t*)dims, (const cuuint64_t*)strides, box, es, CU_TENSOR_MAP_INTERLEAVE_NONE, sw,
      CU_TENSOR_MAP_L2_PROMOTION_L2_256B, CU_TENSOR_MAP_FLOAT_OOB_FILL_NONE);
  return m;
}

extern "C" void kernel_launch(void* const* d_in, const int* in_sizes, int n_in, void* d_out, int out_size) {
  void* fn = nullptr;
  cudaDriverEntryPointQueryResult qr;
  cudaGetDriverEntryPoint("cuTensorMapEncodeTiled", &fn, cudaEnableDefault, &qr);
  EncFn enc = (EncFn)fn;
  void *act, *Y;
  cudaGetSymbolAddress(&act, g_act); cudaGetSymbolAddress(&Y, g_Y);
  uint64_t dx[2] = {D_, S_}, sx[1] = {D_ * 2};
  uint32_t b128[2] = {64, 128}, b16[2] = {64, 16};
  CUtensorMap m_x = mkmap(enc, d_in[0], 2, dx, sx, b128, CU_TENSOR_MAP_SWIZZLE_128B);
  CUtensorMap m_out = mkmap(enc, d_out, 2, dx, sx, b16, CU_TENSOR_MAP_SWIZZLE_128B);
  uint64_t dw1[3] = {32, D_, F_ / 32}, sw1[2] = {F_ * 2, 64};
  uint32_t bw1[3] = {32, 32, 7};
  CUtensorMap m_w1 = mkmap(enc, d_in[7], 3, dw1, sw1, bw1, CU_TENSOR_MAP_SWIZZLE_64B);
  uint64_t da[2] = {F_, S_}, sa[1] = {F_ * 2};
  CUtensorMap m_act = mkmap(enc, act, 2, da, sa, b128, CU_TENSOR_MAP_SWIZZLE_128B);
  uint64_t dw2[5] = {D_, 2, 4, 4, F_ / 32}, sw2[4] = {D_ * 2, 8 * D_ * 2, 2 * D_ * 2, 32 * D_ * 2};
  uint32_t bw2[5] = {64, 2, 4, 4, 2};
  CUtensorMap m_w2 = mkmap(enc, d_in[9], 5, dw2, sw2, bw2, CU_TENSOR_MAP_SWIZZLE_128B);
  uint64_t dy[2] = {S_, D_}, sy[1] = {S_ * 2};
  CUtensorMap m_y = mkmap(enc, Y, 2, dy, sy, b128, CU_TENSOR_MAP_SWIZZLE_128B);
  uint64_t dk[3] = {D_, S_ / 16, 16}, sk[2] = {16 * D_ * 2, D_ * 2};
  uint32_t bkv[3] = {64, 4, 16};
  CUtensorMap m_k = mkmap(enc, d_in[1], 3, dk, sk, bkv, CU_TENSOR_MAP_SWIZZLE_128B);
  CUtensorMap m_v = mkmap(enc, d_in[2], 3, dk, sk, bkv, CU_TENSOR_MAP_SWIZZLE_128B);
  Params p;
  p.x = (const bf16*)d_in[0]; p.k = (const bf16*)d_in[1]; p.v = (const bf16*)d_in[2]; p.shk = (const bf16*)d_in[3];
  p.hk = (const bf16*)d_in[4]; p.Dv = (const bf16*)d_in[5]; p.b1 = (const bf16*)d_in[8]; p.w1 = (const bf16*)d_in[7]; p.zero = 0;
  cudaFuncSetAttribute(fused_kernel, cudaFuncAttributeMaxDynamicSharedMemorySize, SMEM_BYTES);
  fused_kernel<<<128, 384, SMEM_BYTES, cudaStreamPerThread>>>(m_x, m_w1, m_act, m_w2, m_y, m_out, m_k, m_v, p);
}
```

```cpp
#include <cuda_runtime.h>
#include <cuda.h>
#include <cuda_bf16.h>
#include <stdint.h>

typedef __nv_bfloat16 bf16;
typedef __nv_bfloat162 bf162;
constexpr int S_ = 2048, D_ = 1024, F_ = 3584;
constexpr int UARR = 2176, UCH = 2 * UARR;
constexpr int CU0 = 64, CH0 = CU0 + UARR, CU1 = CH0 + 4096 + 64, CH1 = CU1 + UARR, CHB = CH1 + 4096;
constexpr int STAGE = 49152, NST = 4;
constexpr int XOFF = 2 * CHB;
constexpr int SM_XT = NST * STAGE;
constexpr int SM_ST = SM_XT + 32768;
constexpr int SM_CB = SM_ST + 1024;
constexpr int SM_BARS = SM_CB + 1792;
constexpr int SMEM_BYTES = SM_BARS + 256;
constexpr int B1BYTES = 224 * 64 * 2;

__device__ __align__(1024) uint4 g_stat[S_];
__device__ __align__(1024) float g_csp[8 * 16 * 256];
__device__ __align__(1024) bf16 g_act[S_ * F_];
__device__ __align__(1024) uint8_t g_U[(size_t)D_ * UCH];
__device__ __align__(1024) bf16 g_Y[D_ * S_];
__device__ __align__(1024) uint4 g_xch[128 * 8 * 256];
enum { C_U = 0, C_ACT = 16, C_Y = 144, C_TK = 152 };
__device__ unsigned g_cnt[(C_TK + 1) * 32];
#define CSTAMP(k)
#define STAMP(i)
#define STAMP0(i)
#define PSTAMP(i)

#define UITER 16
#define MAPM 1
#define RLD 7
#define UWAIT 4
#define UMASK 0x6600
#define HKL 0
#define UW2 2
#define KVK 20
#define W1K 20
#define HKPF 40
#define XPF 3
#define SPL1 3
#define SPL2 0
#define BIGN 1
#define SIL 4
#define RFPIN 1
#define DCPY 0
#define MISH 1
#define XB16 1
#define HOFF 1
#define PRI 2
#define PRK 14
#define FDUP 1
#define SHAD 2
#define SRS 1
#define PARTX (MAPM ? 64 : 8)
__device__ __forceinline__ void mma_n224(float (&d)[112], uint32_t da, uint32_t db, int sd) {
  asm volatile("{\n.reg .pred p;\n.reg .b64 a, b;\nsetp.ne.b32 p, %114, 0;\nmov.b64 a, {%112, 0x40000040};\nmov.b64 b, {%113, 0x80000020};\n"
    "wgmma.mma_async.sync.aligned.m64n224k16.f32.bf16.bf16 {%0,%1,%2,%3,%4,%5,%6,%7,%8,%9,%10,%11,%12,%13,%14,%15,%16,%17,%18,%19,%20,%21,%22,%23,%24,%25,%26,%27,%28,%29,%30,%31,%32,%33,%34,%35,%36,%37,%38,%39,%40,%41,%42,%43,%44,%45,%46,%47,%48,%49,%50,%51,%52,%53,%54,%55,%56,%57,%58,%59,%60,%61,%62,%63,%64,%65,%66,%67,%68,%69,%70,%71,%72,%73,%74,%75,%76,%77,%78,%79,%80,%81,%82,%83,%84,%85,%86,%87,%88,%89,%90,%91,%92,%93,%94,%95,%96,%97,%98,%99,%100,%101,%102,%103,%104,%105,%106,%107,%108,%109,%110,%111}, a, b, p, 1, 1, 0, 1;\n}\n"
    : "+f"(d[0]),"+f"(d[1]),"+f"(d[2]),"+f"(d[3]),"+f"(d[4]),"+f"(d[5]),"+f"(d[6]),"+f"(d[7]),"+f"(d[8]),"+f"(d[9]),"+f"(d[10]),"+f"(d[11]),"+f"(d[12]),"+f"(d[13]),"+f"(d[14]),"+f"(d[15]),"+f"(d[16]),"+f"(d[17]),"+f"(d[18]),"+f"(d[19]),"+f"(d[20]),"+f"(d[21]),"+f"(d[22]),"+f"(d[23]),"+f"(d[24]),"+f"(d[25]),"+f"(d[26]),"+f"(d[27]),"+f"(d[28]),"+f"(d[29]),"+f"(d[30]),"+f"(d[31]),"+f"(d[32]),"+f"(d[33]),"+f"(d[34]),"+f"(d[35]),"+f"(d[36]),"+f"(d[37]),"+f"(d[38]),"+f"(d[39]),"+f"(d[40]),"+f"(d[41]),"+f"(d[42]),"+f"(d[43]),"+f"(d[44]),"+f"(d[45]),"+f"(d[46]),"+f"(d[47]),"+f"(d[48]),"+f"(d[49]),"+f"(d[50]),"+f"(d[51]),"+f"(d[52]),"+f"(d[53]),"+f"(d[54]),"+f"(d[55]),"+f"(d[56]),"+f"(d[57]),"+f"(d[58]),"+f"(d[59]),"+f"(d[60]),"+f"(d[61]),"+f"(d[62]),"+f"(d[63]),"+f"(d[64]),"+f"(d[65]),"+f"(d[66]),"+f"(d[67]),"+f"(d[68]),"+f"(d[69]),"+f"(d[70]),"+f"(d[71]),"+f"(d[72]),"+f"(d[73]),"+f"(d[74]),"+f"(d[75]),"+f"(d[76]),"+f"(d[77]),"+f"(d[78]),"+f"(d[79]),"+f"(d[80]),"+f"(d[81]),"+f"(d[82]),"+f"(d[83]),"+f"(d[84]),"+f"(d[85]),"+f"(d[86]),"+f"(d[87]),"+f"(d[88]),"+f"(d[89]),"+f"(d[90]),"+f"(d[91]),"+f"(d[92]),"+f"(d[93]),"+f"(d[94]),"+f"(d[95]),"+f"(d[96]),"+f"(d[97]),"+f"(d[98]),"+f"(d[99]),"+f"(d[100]),"+f"(d[101]),"+f"(d[102]),"+f"(d[103]),"+f"(d[104]),"+f"(d[105]),"+f"(d[106]),"+f"(d[107]),"+f"(d[108]),"+f"(d[109]),"+f"(d[110]),"+f"(d[111])
    : "r"(da), "r"(db), "r"(sd));
}
__device__ __forceinline__ void mma_n256(float (&d)[128], uint32_t da, uint32_t db, int sd) {
  asm volatile("{\n.reg .pred p;\n.reg .b64 a, b;\nsetp.ne.b32 p, %130, 0;\nmov.b64 a, {%128, 0x40000040};\nmov.b64 b, {%129, 0x40000040};\n"
    "wgmma.mma_async.sync.aligned.m64n256k16.f32.bf16.bf16 {%0,%1,%2,%3,%4,%5,%6,%7,%8,%9,%10,%11,%12,%13,%14,%15,%16,%17,%18,%19,%20,%21,%22,%23,%24,%25,%26,%27,%28,%29,%30,%31,%32,%33,%34,%35,%36,%37,%38,%39,%40,%41,%42,%43,%44,%45,%46,%47,%48,%49,%50,%51,%52,%53,%54,%55,%56,%57,%58,%59,%60,%61,%62,%63,%64,%65,%66,%67,%68,%69,%70,%71,%72,%73,%74,%75,%76,%77,%78,%79,%80,%81,%82,%83,%84,%85,%86,%87,%88,%89,%90,%91,%92,%93,%94,%95,%96,%97,%98,%99,%100,%101,%102,%103,%104,%105,%106,%107,%108,%109,%110,%111,%112,%113,%114,%115,%116,%117,%118,%119,%120,%121,%122,%123,%124,%125,%126,%127}, a, b, p, 1, 1, 0, 1;\n}\n"
    : "+f"(d[0]),"+f"(d[1]),"+f"(d[2]),"+f"(d[3]),"+f"(d[4]),"+f"(d[5]),"+f"(d[6]),"+f"(d[7]),"+f"(d[8]),"+f"(d[9]),"+f"(d[10]),"+f"(d[11]),"+f"(d[12]),"+f"(d[13]),"+f"(d[14]),"+f"(d[15]),"+f"(d[16]),"+f"(d[17]),"+f"(d[18]),"+f"(d[19]),"+f"(d[20]),"+f"(d[21]),"+f"(d[22]),"+f"(d[23]),"+f"(d[24]),"+f"(d[25]),"+f"(d[26]),"+f"(d[27]),"+f"(d[28]),"+f"(d[29]),"+f"(d[30]),"+f"(d[31]),"+f"(d[32]),"+f"(d[33]),"+f"(d[34]),"+f"(d[35]),"+f"(d[36]),"+f"(d[37]),"+f"(d[38]),"+f"(d[39]),"+f"(d[40]),"+f"(d[41]),"+f"(d[42]),"+f"(d[43]),"+f"(d[44]),"+f"(d[45]),"+f"(d[46]),"+f"(d[47]),"+f"(d[48]),"+f"(d[49]),"+f"(d[50]),"+f"(d[51]),"+f"(d[52]),"+f"(d[53]),"+f"(d[54]),"+f"(d[55]),"+f"(d[56]),"+f"(d[57]),"+f"(d[58]),"+f"(d[59]),"+f"(d[60]),"+f"(d[61]),"+f"(d[62]),"+f"(d[63]),"+f"(d[64]),"+f"(d[65]),"+f"(d[66]),"+f"(d[67]),"+f"(d[68]),"+f"(d[69]),"+f"(d[70]),"+f"(d[71]),"+f"(d[72]),"+f"(d[73]),"+f"(d[74]),"+f"(d[75]),"+f"(d[76]),"+f"(d[77]),"+f"(d[78]),"+f"(d[79]),"+f"(d[80]),"+f"(d[81]),"+f"(d[82]),"+f"(d[83]),"+f"(d[84]),"+f"(d[85]),"+f"(d[86]),"+f"(d[87]),"+f"(d[88]),"+f"(d[89]),"+f"(d[90]),"+f"(d[91]),"+f"(d[92]),"+f"(d[93]),"+f"(d[94]),"+f"(d[95]),"+f"(d[96]),"+f"(d[97]),"+f"(d[98]),"+f"(d[99]),"+f"(d[100]),"+f"(d[101]),"+f"(d[102]),"+f"(d[103]),"+f"(d[104]),"+f"(d[105]),"+f"(d[106]),"+f"(d[107]),"+f"(d[108]),"+f"(d[109]),"+f"(d[110]),"+f"(d[111]),"+f"(d[112]),"+f"(d[113]),"+f"(d[114]),"+f"(d[115]),"+f"(d[116]),"+f"(d[117]),"+f"(d[118]),"+f"(d[119]),"+f"(d[120]),"+f"(d[121]),"+f"(d[122]),"+f"(d[123]),"+f"(d[124]),"+f"(d[125]),"+f"(d[126]),"+f"(d[127])
    : "r"(da), "r"(db), "r"(sd));
}
__device__ __forceinline__ void mma_n128(float (&d)[128], uint32_t da, uint32_t db, int sd) {
  asm volatile("{\n.reg .pred p;\n.reg .b64 a, b;\nsetp.ne.b32 p, %66, 0;\nmov.b64 a, {%64, 0x40000040};\nmov.b64 b, {%65, 0x40000040};\n"
    "wgmma.mma_async.sync.aligned.m64n128k16.f32.bf16.bf16 {%0,%1,%2,%3,%4,%5,%6,%7,%8,%9,%10,%11,%12,%13,%14,%15,%16,%17,%18,%19,%20,%21,%22,%23,%24,%25,%26,%27,%28,%29,%30,%31,%32,%33,%34,%35,%36,%37,%38,%39,%40,%41,%42,%43,%44,%45,%46,%47,%48,%49,%50,%51,%52,%53,%54,%55,%56,%57,%58,%59,%60,%61,%62,%63}, a, b, p, 1, 1, 0, 1;\n}\n"
    : "+f"(d[0]),"+f"(d[1]),"+f"(d[2]),"+f"(d[3]),"+f"(d[4]),"+f"(d[5]),"+f"(d[6]),"+f"(d[7]),"+f"(d[8]),"+f"(d[9]),"+f"(d[10]),"+f"(d[11]),"+f"(d[12]),"+f"(d[13]),"+f"(d[14]),"+f"(d[15]),"+f"(d[16]),"+f"(d[17]),"+f"(d[18]),"+f"(d[19]),"+f"(d[20]),"+f"(d[21]),"+f"(d[22]),"+f"(d[23]),"+f"(d[24]),"+f"(d[25]),"+f"(d[26]),"+f"(d[27]),"+f"(d[28]),"+f"(d[29]),"+f"(d[30]),"+f"(d[31]),"+f"(d[32]),"+f"(d[33]),"+f"(d[34]),"+f"(d[35]),"+f"(d[36]),"+f"(d[37]),"+f"(d[38]),"+f"(d[39]),"+f"(d[40]),"+f"(d[41]),"+f"(d[42]),"+f"(d[43]),"+f"(d[44]),"+f"(d[45]),"+f"(d[46]),"+f"(d[47]),"+f"(d[48]),"+f"(d[49]),"+f"(d[50]),"+f"(d[51]),"+f"(d[52]),"+f"(d[53]),"+f"(d[54]),"+f"(d[55]),"+f"(d[56]),"+f"(d[57]),"+f"(d[58]),"+f"(d[59]),"+f"(d[60]),"+f"(d[61]),"+f"(d[62]),"+f"(d[63])
    : "r"(da), "r"(db), "r"(sd));
}
__device__ __forceinline__ void cmma(float (&d)[16], uint32_t a0, uint32_t a1, uint32_t a2, uint32_t a3, uint32_t db, int sd) {
  asm volatile("{\n.reg .pred p;\n.reg .b64 b;\nsetp.ne.b32 p, %21, 0;\nmov.b64 b, {%20, 8};\n"
    "wgmma.mma_async.sync.aligned.m64n32k16.f32.bf16.bf16 {%0,%1,%2,%3,%4,%5,%6,%7,%8,%9,%10,%11,%12,%13,%14,%15}, {%16,%17,%18,%19}, b, p, 1, 1, 0;\n}\n"
    : "+f"(d[0]),"+f"(d[1]),"+f"(d[2]),"+f"(d[3]),"+f"(d[4]),"+f"(d[5]),"+f"(d[6]),"+f"(d[7]),"+f"(d[8]),"+f"(d[9]),"+f"(d[10]),"+f"(d[11]),"+f"(d[12]),"+f"(d[13]),"+f"(d[14]),"+f"(d[15])
    : "r"(a0), "r"(a1), "r"(a2), "r"(a3), "r"(db), "r"(sd));
}
__device__ __forceinline__ void cmma128(float (&d)[64], uint32_t a0, uint32_t a1, uint32_t a2, uint32_t a3, uint32_t db, int sd) {
  asm volatile("{\n.reg .pred p;\n.reg .b64 b;\nsetp.ne.b32 p, %69, 0;\nmov.b64 b, {%68, 8};\n"
    "wgmma.mma_async.sync.aligned.m64n128k16.f32.bf16.bf16 {%0,%1,%2,%3,%4,%5,%6,%7,%8,%9,%10,%11,%12,%13,%14,%15,%16,%17,%18,%19,%20,%21,%22,%23,%24,%25,%26,%27,%28,%29,%30,%31,%32,%33,%34,%35,%36,%37,%38,%39,%40,%41,%42,%43,%44,%45,%46,%47,%48,%49,%50,%51,%52,%53,%54,%55,%56,%57,%58,%59,%60,%61,%62,%63}, {%64,%65,%66,%67}, b, p, 1, 1, 0;\n}\n"
    : "+f"(d[0]),"+f"(d[1]),"+f"(d[2]),"+f"(d[3]),"+f"(d[4]),"+f"(d[5]),"+f"(d[6]),"+f"(d[7]),"+f"(d[8]),"+f"(d[9]),"+f"(d[10]),"+f"(d[11]),"+f"(d[12]),"+f"(d[13]),"+f"(d[14]),"+f"(d[15]),"+f"(d[16]),"+f"(d[17]),"+f"(d[18]),"+f"(d[19]),"+f"(d[20]),"+f"(d[21]),"+f"(d[22]),"+f"(d[23]),"+f"(d[24]),"+f"(d[25]),"+f"(d[26]),"+f"(d[27]),"+f"(d[28]),"+f"(d[29]),"+f"(d[30]),"+f"(d[31]),"+f"(d[32]),"+f"(d[33]),"+f"(d[34]),"+f"(d[35]),"+f"(d[36]),"+f"(d[37]),"+f"(d[38]),"+f"(d[39]),"+f"(d[40]),"+f"(d[41]),"+f"(d[42]),"+f"(d[43]),"+f"(d[44]),"+f"(d[45]),"+f"(d[46]),"+f"(d[47]),"+f"(d[48]),"+f"(d[49]),"+f"(d[50]),"+f"(d[51]),"+f"(d[52]),"+f"(d[53]),"+f"(d[54]),"+f"(d[55]),"+f"(d[56]),"+f"(d[57]),"+f"(d[58]),"+f"(d[59]),"+f"(d[60]),"+f"(d[61]),"+f"(d[62]),"+f"(d[63])
    : "r"(a0), "r"(a1), "r"(a2), "r"(a3), "r"(db), "r"(sd));
}
__device__ __forceinline__ void cmma96(float (&d)[64], uint32_t a0, uint32_t a1, uint32_t a2, uint32_t a3, uint32_t db, int sd) {
  asm volatile("{\n.reg .pred p;\n.reg .b64 b;\nsetp.ne.b32 p, %53, 0;\nmov.b64 b, {%52, 8};\n"
    "wgmma.mma_async.sync.aligned.m64n96k16.f32.bf16.bf16 {%0,%1,%2,%3,%4,%5,%6,%7,%8,%9,%10,%11,%12,%13,%14,%15,%16,%17,%18,%19,%20,%21,%22,%23,%24,%25,%26,%27,%28,%29,%30,%31,%32,%33,%34,%35,%36,%37,%38,%39,%40,%41,%42,%43,%44,%45,%46,%47}, {%48,%49,%50,%51}, b, p, 1, 1, 0;\n}\n"
    : "+f"(d[0]),"+f"(d[1]),"+f"(d[2]),"+f"(d[3]),"+f"(d[4]),"+f"(d[5]),"+f"(d[6]),"+f"(d[7]),"+f"(d[8]),"+f"(d[9]),"+f"(d[10]),"+f"(d[11]),"+f"(d[12]),"+f"(d[13]),"+f"(d[14]),"+f"(d[15]),"+f"(d[16]),"+f"(d[17]),"+f"(d[18]),"+f"(d[19]),"+f"(d[20]),"+f"(d[21]),"+f"(d[22]),"+f"(d[23]),"+f"(d[24]),"+f"(d[25]),"+f"(d[26]),"+f"(d[27]),"+f"(d[28]),"+f"(d[29]),"+f"(d[30]),"+f"(d[31]),"+f"(d[32]),"+f"(d[33]),"+f"(d[34]),"+f"(d[35]),"+f"(d[36]),"+f"(d[37]),"+f"(d[38]),"+f"(d[39]),"+f"(d[40]),"+f"(d[41]),"+f"(d[42]),"+f"(d[43]),"+f"(d[44]),"+f"(d[45]),"+f"(d[46]),"+f"(d[47])
    : "r"(a0), "r"(a1), "r"(a2), "r"(a3), "r"(db), "r"(sd));
}
__device__ __forceinline__ void cmma64(float (&d)[64], uint32_t a0, uint32_t a1, uint32_t a2, uint32_t a3, uint32_t db, int sd) {
  asm volatile("{\n.reg .pred p;\n.reg .b64 b;\nsetp.ne.b32 p, %37, 0;\nmov.b64 b, {%36, 8};\n"
    "wgmma.mma_async.sync.aligned.m64n64k16.f32.bf16.bf16 {%0,%1,%2,%3,%4,%5,%6,%7,%8,%9,%10,%11,%12,%13,%14,%15,%16,%17,%18,%19,%20,%21,%22,%23,%24,%25,%26,%27,%28,%29,%30,%31}, {%32,%33,%34,%35}, b, p, 1, 1, 0;\n}\n"
    : "+f"(d[0]),"+f"(d[1]),"+f"(d[2]),"+f"(d[3]),"+f"(d[4]),"+f"(d[5]),"+f"(d[6]),"+f"(d[7]),"+f"(d[8]),"+f"(d[9]),"+f"(d[10]),"+f"(d[11]),"+f"(d[12]),"+f"(d[13]),"+f"(d[14]),"+f"(d[15]),"+f"(d[16]),"+f"(d[17]),"+f"(d[18]),"+f"(d[19]),"+f"(d[20]),"+f"(d[21]),"+f"(d[22]),"+f"(d[23]),"+f"(d[24]),"+f"(d[25]),"+f"(d[26]),"+f"(d[27]),"+f"(d[28]),"+f"(d[29]),"+f"(d[30]),"+f"(d[31])
    : "r"(a0), "r"(a1), "r"(a2), "r"(a3), "r"(db), "r"(sd));
}
__device__ __forceinline__ void cmma32(float (&d)[64], uint32_t a0, uint32_t a1, uint32_t a2, uint32_t a3, uint32_t db, int sd) {
  asm volatile("{\n.reg .pred p;\n.reg .b64 b;\nsetp.ne.b32 p, %21, 0;\nmov.b64 b, {%20, 8};\n"
    "wgmma.mma_async.sync.aligned.m64n32k16.f32.bf16.bf16 {%0,%1,%2,%3,%4,%5,%6,%7,%8,%9,%10,%11,%12,%13,%14,%15}, {%16,%17,%18,%19}, b, p, 1, 1, 0;\n}\n"
    : "+f"(d[0]),"+f"(d[1]),"+f"(d[2]),"+f"(d[3]),"+f"(d[4]),"+f"(d[5]),"+f"(d[6]),"+f"(d[7]),"+f"(d[8]),"+f"(d[9]),"+f"(d[10]),"+f"(d[11]),"+f"(d[12]),"+f"(d[13]),"+f"(d[14]),"+f"(d[15])
    : "r"(a0), "r"(a1), "r"(a2), "r"(a3), "r"(db), "r"(sd));
}

__device__ __forceinline__ void wg_fence() { asm volatile("wgmma.fence.sync.aligned;" ::: "memory"); }
__device__ __forceinline__ void wg_commit() { asm volatile("wgmma.commit_group.sync.aligned;" ::: "memory"); }
template <int N> __device__ __forceinline__ void wg_wait() { asm volatile("wgmma.wait_group.sync.aligned %0;" ::"n"(N) : "memory"); }
__device__ __forceinline__ uint32_t mkdesc(uint32_t addr, uint32_t lbo) { return ((addr & 0x3FFFF) >> 4) | ((lbo >> 4) << 16); }
__device__ __forceinline__ uint32_t smem_u32(const void* p) { return (uint32_t)__cvta_generic_to_shared(p); }
__device__ __forceinline__ void mbar_init(uint32_t bar, uint32_t cnt) { asm volatile("mbarrier.init.shared::cta.b64 [%0], %1;" ::"r"(bar), "r"(cnt) : "memory"); }
__device__ __forceinline__ void mbar_expect_tx(uint32_t bar, uint32_t bytes) { asm volatile("mbarrier.arrive.expect_tx.shared::cta.b64 _, [%0], %1;" ::"r"(bar), "r"(bytes) : "memory"); }
__device__ __forceinline__ void mbar_arrive(uint32_t bar) { asm volatile("mbarrier.arrive.shared::cta.b64 _, [%0];" ::"r"(bar) : "memory"); }
__device__ __forceinline__ uint32_t mapa(uint32_t a, uint32_t cta) { uint32_t r; asm volatile("mapa.shared::cluster.u32 %0, %1, %2;" : "=r"(r) : "r"(a), "r"(cta)); return r; }
__device__ __forceinline__ void mbar_arrive_remote(uint32_t rbar) { asm volatile("mbarrier.arrive.shared::cluster.b64 _, [%0];" ::"r"(rbar) : "memory"); }
__device__ __forceinline__ void mbar_arrive_remote4(uint32_t rbar) { asm volatile("mbarrier.arrive.shared::cluster.b64 _, [%0], 4;" ::"r"(rbar) : "memory"); }
__device__ __forceinline__ void mbar_wait(uint32_t bar, uint32_t parity) {
  asm volatile("{\n.reg .pred p;\n.reg .u32 n;\nmov.u32 n, 0;\nLW:\nmbarrier.try_wait.parity.shared::cta.b64 p, [%0], %1;\n@p bra LD;\n"
               "add.u32 n, n, 1;\nsetp.lt.u32 p, n, 4000000;\n@p bra LW;\ntrap;\nLD:\n}\n" ::"r"(bar), "r"(parity) : "memory");
}
__device__ __forceinline__ void tma2d(uint32_t dst, const CUtensorMap* m, uint32_t bar, int c0, int c1) {
  asm volatile("cp.async.bulk.tensor.2d.shared::cluster.global.mbarrier::complete_tx::bytes [%0], [%1, {%3, %4}], [%2];" ::"r"(dst), "l"(m), "r"(bar), "r"(c0), "r"(c1) : "memory");
}
__device__ __forceinline__ void tma3d_mc(uint32_t dst, const CUtensorMap* m, uint32_t bar, int c0, int c1, int c2, uint16_t mask) {
  asm volatile("cp.async.bulk.tensor.3d.shared::cluster.global.mbarrier::complete_tx::bytes.multicast::cluster [%0], [%1, {%3, %4, %5}], [%2], %6;" ::"r"(dst), "l"(m), "r"(bar), "r"(c0), "r"(c1), "r"(c2), "h"(mask) : "memory");
}
__device__ __forceinline__ void tma5d_mc(uint32_t dst, const CUtensorMap* m, uint32_t bar, int c0, int c4) {
  asm volatile("cp.async.bulk.tensor.5d.shared::cluster.global.mbarrier::complete_tx::bytes.multicast::cluster [%0], [%1, {%3, %5, %5, %5, %4}], [%2], %6;" ::"r"(dst), "l"(m), "r"(bar), "r"(c0), "r"(c4), "r"(0), "h"((uint16_t)3) : "memory");
}
__device__ __forceinline__ void tma2d_store(const CUtensorMap* m, uint32_t src, int c0, int c1) {
  asm volatile("cp.async.bulk.tensor.2d.global.shared::cta.bulk_group [%0, {%2, %3}], [%1];" ::"l"(m), "r"(src), "r"(c0), "r"(c1) : "memory");
}
__device__ __forceinline__ void bulk_g2s(uint32_t dst, const void* src, uint32_t bytes, uint32_t bar) {
  asm volatile("cp.async.bulk.shared::cluster.global.mbarrier::complete_tx::bytes [%0], [%1], %2, [%3];" ::"r"(dst), "l"(src), "r"(bytes), "r"(bar) : "memory");
}
__device__ __forceinline__ void fence_async() { asm volatile("fence.proxy.async.global;" ::: "memory"); }
__device__ __forceinline__ void bar_sync(int id, int n) { asm volatile("bar.sync %0, %1;" ::"r"(id), "r"(n) : "memory"); }
__device__ __forceinline__ void bar_arrive(int id, int n) { asm volatile("bar.arrive %0, %1;" ::"r"(id), "r"(n) : "memory"); }
__device__ __forceinline__ uint32_t lds32(uint32_t a) { uint32_t v; asm volatile("ld.volatile.shared.b32 %0, [%1];" : "=r"(v) : "r"(a)); return v; }
__device__ __forceinline__ void sts128(uint32_t a, float x, float y, float z, float w) { asm volatile("st.shared.v4.f32 [%0], {%1,%2,%3,%4};" ::"r"(a), "f"(x), "f"(y), "f"(z), "f"(w) : "memory"); }
__device__ __forceinline__ void sts64(uint32_t a, uint32_t x, uint32_t y) { asm volatile("st.shared.v2.b32 [%0], {%1,%2};" ::"r"(a), "r"(x), "r"(y) : "memory"); }
template <int OFF> __device__ __forceinline__ uint2 lds64p(uint32_t a, bool on) {
  uint2 v;
  asm volatile("{\n.reg .pred p;\nsetp.ne.s32 p, %3, 0;\nmov.u32 %0, 0;\nmov.u32 %1, 0;\n@p ld.shared.v2.b32 {%0,%1}, [%2+%4];\n}\n" : "=r"(v.x), "=r"(v.y) : "r"(a), "r"((int)on), "n"(OFF) : "memory");
  return v;
}
__device__ __forceinline__ uint2 lds64(uint32_t a) { uint2 v; asm volatile("ld.shared.v2.b32 {%0,%1}, [%2];" : "=r"(v.x), "=r"(v.y) : "r"(a) : "memory"); return v; }
__device__ __forceinline__ float4 lds128(uint32_t a) { float4 v; asm volatile("ld.shared.v4.f32 {%0,%1,%2,%3}, [%4];" : "=f"(v.x), "=f"(v.y), "=f"(v.z), "=f"(v.w) : "r"(a) : "memory"); return v; }
__device__ __forceinline__ void stg128(void* p, uint32_t a, uint32_t b, uint32_t c, uint32_t d) { asm volatile("st.global.v4.b32 [%0], {%1,%2,%3,%4};" ::"l"(p), "r"(a), "r"(b), "r"(c), "r"(d) : "memory"); }
__device__ __forceinline__ void sts128u(uint32_t a, uint32_t x, uint32_t y, uint32_t z, uint32_t w) { asm volatile("st.shared.v4.b32 [%0], {%1,%2,%3,%4};" ::"r"(a), "r"(x), "r"(y), "r"(z), "r"(w) : "memory"); }
__device__ __forceinline__ void signal(int c, unsigned inc) { asm volatile("red.release.gpu.global.add.u32 [%0], %1;" ::"l"(g_cnt + c * 32), "r"(inc) : "memory"); }
__device__ __forceinline__ unsigned ld_epoch() { unsigned v; asm volatile("ld.relaxed.gpu.global.u32 %0, [%1];" : "=r"(v) : "l"(g_cnt + C_TK * 32) : "memory"); return (v >> 7) + 1; }
constexpr int SPINMAX = 1000000;
__device__ __forceinline__ void spin_guard(int n) { asm volatile("{\n.reg .pred p;\nsetp.gt.s32 p, %0, 1000000;\n@p trap;\n}\n" ::"r"(n)); }
__device__ __forceinline__ void wait_cnt(int c, unsigned ep) {
  unsigned v, n = 0;
  while (true) {
    asm volatile("ld.acquire.gpu.global.u32 %0, [%1];" : "=r"(v) : "l"(g_cnt + c * 32) : "memory");
    if ((int)(v - (ep << 7)) >= 0) break;
    spin_guard(++n);
    __nanosleep(20);
  }
}
__device__ __forceinline__ uint4 ldg128_rlx(const void* p) { uint4 v; asm volatile("ld.relaxed.gpu.global.v4.b32 {%0,%1,%2,%3}, [%4];" : "=r"(v.x), "=r"(v.y), "=r"(v.z), "=r"(v.w) : "l"(p) : "memory"); return v; }
__device__ __forceinline__ uint2 ldg64_rlx(const void* p) { uint2 v; asm volatile("ld.relaxed.gpu.global.v2.b32 {%0,%1}, [%2];" : "=r"(v.x), "=r"(v.y) : "l"(p) : "memory"); return v; }
__device__ __forceinline__ void stg64_rlx(void* p, uint32_t a, uint32_t b) { asm volatile("st.relaxed.gpu.global.v2.b32 [%0], {%1,%2};" ::"l"(p), "r"(a), "r"(b) : "memory"); }
__device__ __forceinline__ void stg128_rlx(void* p, uint32_t a, uint32_t b, uint32_t c, uint32_t d) { asm volatile("st.relaxed.gpu.global.v4.b32 [%0], {%1,%2,%3,%4};" ::"l"(p), "r"(a), "r"(b), "r"(c), "r"(d) : "memory"); }
__device__ __forceinline__ uint32_t pack2(float lo, float hi) { uint32_t r; asm("cvt.rn.bf16x2.f32 %0, %1, %2;" : "=r"(r) : "f"(hi), "f"(lo)); return r; }
__device__ __forceinline__ float blo(uint32_t v) { return __uint_as_float(v << 16); }
__device__ __forceinline__ float bhi(uint32_t v) { return __uint_as_float(v & 0xffff0000u); }
__device__ __forceinline__ float rbf(float x) { return __bfloat162float(__float2bfloat16_rn(x)); }
__device__ __forceinline__ uint32_t hmul2(uint32_t a, uint32_t b) { uint32_t r; asm("mul.rn.bf16x2 %0, %1, %2;" : "=r"(r) : "r"(a), "r"(b)); return r; }
__device__ __forceinline__ uint32_t hadd2(uint32_t a, uint32_t b) { uint32_t r; asm("add.rn.bf16x2 %0, %1, %2;" : "=r"(r) : "r"(a), "r"(b)); return r; }
__device__ __forceinline__ uint32_t hfma2(uint32_t a, uint32_t b, uint32_t c) { uint32_t r; asm("fma.rn.bf16x2 %0, %1, %2, %3;" : "=r"(r) : "r"(a), "r"(b), "r"(c)); return r; }
__device__ __forceinline__ uint32_t ldg32(const void* p) { uint32_t v; asm volatile("ld.global.nc.b32 %0, [%1];" : "=r"(v) : "l"(p)); return v; }
__device__ __forceinline__ uint4 ldg128(const void* p) { uint4 v; asm volatile("ld.global.nc.v4.b32 {%0,%1,%2,%3}, [%4];" : "=r"(v.x), "=r"(v.y), "=r"(v.z), "=r"(v.w) : "l"(p)); return v; }
__device__ __forceinline__ uint2 ldg64(const void* p) { uint2 v; asm volatile("ld.global.nc.v2.b32 {%0,%1}, [%2];" : "=r"(v.x), "=r"(v.y) : "l"(p)); return v; }
__device__ __forceinline__ uint32_t ldg16(const void* p, int on) { uint32_t v; asm volatile("{\n.reg .pred p;\nsetp.ne.s32 p, %2, 0;\nmov.u32 %0, 0;\n@p ld.global.nc.u16 %0, [%1];\n}\n" : "=r"(v) : "l"(p), "r"(on)); return v; }
__device__ __forceinline__ void tma3d(uint32_t dst, const CUtensorMap* m, uint32_t bar, int c0, int c1) {
  asm volatile("cp.async.bulk.tensor.3d.shared::cluster.global.mbarrier::complete_tx::bytes [%0], [%1, {%3, %4, %5}], [%2];" ::"r"(dst), "l"(m), "r"(bar), "r"(c0), "r"(c1), "r"(0) : "memory");
}
__device__ __forceinline__ void ldsm4t(uint32_t* r, uint32_t a) { asm volatile("ldmatrix.sync.aligned.m8n8.x4.trans.shared.b16 {%0,%1,%2,%3}, [%4];" : "=r"(r[0]), "=r"(r[1]), "=r"(r[2]), "=r"(r[3]) : "r"(a) : "memory"); }
__device__ __forceinline__ uint32_t movm(uint32_t v) { uint32_t r; asm volatile("movmatrix.sync.aligned.m8n8.trans.b16 %0, %1;" : "=r"(r) : "r"(v)); return r; }
__device__ __forceinline__ float ex2(float x) { float r; asm("ex2.approx.ftz.f32 %0, %1;" : "=f"(r) : "f"(x)); return r; }
__device__ __forceinline__ float rcp(float x) { float r; asm("rcp.approx.ftz.f32 %0, %1;" : "=f"(r) : "f"(x)); return r; }
constexpr float LOG2E = 1.4426950408889634f;
__device__ __forceinline__ float mish(float h) {
  float u = ex2(h * 1.4426950408889634f) + 1.f;
  return h * fmaf(rcp(fmaf(u, u, 1.f)), -2.f, 1.f);
}
__device__ __forceinline__ void silu4(float (&t)[4]) {
  float a[4];
#pragma unroll
  for (int i = 0; i < 4; i++) a[i] = 1.f + ex2(fminf(t[i], 31.f));
  const float p = a[0] * a[1], q = a[2] * a[3], r = rcp(p * q) * -0.6931471805599453f, rp = r * q, rq = r * p;
  t[0] *= a[1] * rp; t[1] *= a[0] * rp; t[2] *= a[3] * rq; t[3] *= a[2] * rq;
}

__device__ __forceinline__ uint32_t cpy(uint32_t v, uint32_t z) { uint32_t r; asm volatile("mad.lo.u32 %0, %1, %2, 0;" : "=r"(r) : "r"(v), "r"(z + 1)); return r; }
__device__ __forceinline__ uint32_t cpx(uint32_t v, uint32_t z) { uint32_t r; asm volatile("xor.b32 %0, %1, %2;" : "=r"(r) : "r"(v), "r"(z)); return r; }
template <int HG> __device__ __forceinline__ void loadP(uint32_t (&x)[16], uint32_t hb, int p) {
  const uint32_t b = hb + (HG >> 1) * 1024 + (HG & 1) * 128;
#pragma unroll
  for (int j = 3 * p; j < 3 * p + 3; j++) x[j ? 2 * j - 1 : 0] = lds32(b + j * 16);
}
template <int HG> __device__ __forceinline__ void loadA(uint32_t (&x)[16], uint32_t hb) { loadP<HG>(x, hb, 0); loadP<HG>(x, hb, 1); loadP<HG>(x, hb, 2); }
__device__ __forceinline__ void dupA(uint32_t (&x)[16], uint32_t z) {
#pragma unroll
  for (int r = 0; r < 4; r++) { x[4 * r + 2] = cpy(x[4 * r + 1], z); if (r < 3) x[4 * r + 4] = cpx(x[4 * r + 3], z); }
}
template <int HG> __device__ __forceinline__ void mmaG(float (&d)[64], uint32_t (&x)[16], uint32_t dbase) {
  wg_fence();
#pragma unroll
  for (int rr = 0; rr < 4; rr++) {
    constexpr int SP = HG >> 1;
    const uint32_t db = dbase + (SP * 32 + (HG & 1) * 4 + rr);
    const int sd = (HG | rr) != 0;
    if (SP == 0) cmma128(d, x[4 * rr], x[4 * rr + 1], x[4 * rr + 2], x[4 * rr + 3], db, sd);
    if (SP == 1) cmma96(d, x[4 * rr], x[4 * rr + 1], x[4 * rr + 2], x[4 * rr + 3], db, sd);
    if (SP == 2) cmma64(d, x[4 * rr], x[4 * rr + 1], x[4 * rr + 2], x[4 * rr + 3], db, sd);
    if (SP == 3) cmma32(d, x[4 * rr], x[4 * rr + 1], x[4 * rr + 2], x[4 * rr + 3], db, sd);
  }
  wg_commit();
}

struct Params {
  const bf16 *x, *k, *v, *shk, *hk, *Dv, *b1, *w1;
  uint32_t zero;
};

__device__ __forceinline__ void act_chunk(const uint32_t* h, bf16* dst) {
  uint32_t o[4];
#pragma unroll
  for (int i = 0; i < 4; i++) o[i] = pack2(mish(blo(h[i])), mish(bhi(h[i])));
  stg128(dst, o[0], o[1], o[2], o[3]);
}

#define LOCALS const uint32_t tid = threadIdx.x; \
  const int lane = tid & 31, w = (tid >> 5) & 3, g = lane >> 2, q = lane & 3, wg = tid >> 7; (void)w; (void)g; (void)q; (void)wg

#define WGU __shfl_sync(0xffffffff, wg, 0)
enum { NB_ORD0 = 1, NB_ORD1 = 2, NB_WG0 = 3, NB_WG1 = 4, NB_CS = 5, NB_ACT = 6, NB_Y = 7, NB_U = 11, NB_ST = 12, NB_PRI = 13 };

__global__ void __cluster_dims__(2, 1, 1) __launch_bounds__(384, 1)
fused_kernel(const __grid_constant__ CUtensorMap m_x, const __grid_constant__ CUtensorMap m_w1, const __grid_constant__ CUtensorMap m_act,
             const __grid_constant__ CUtensorMap m_w2, const __grid_constant__ CUtensorMap m_y, const __grid_constant__ CUtensorMap m_out,
             const __grid_constant__ CUtensorMap m_k, const __grid_constant__ CUtensorMap m_v, const Params p) {
  extern __shared__ __align__(1024) uint8_t smem_raw[];
  const uint32_t sb = smem_u32(smem_raw);
  const uint32_t bfull = sb + SM_BARS, bempty = bfull + 32, bepi = bfull + 64, bxt = bfull + 72, byf = bfull + 80, bdep = bfull + 88, bkv = bfull + 136, bhl = bfull + 152, bh = bfull + 184, bkf = bfull + 216, s_par = bfull + 224, bdx = bfull + 232;
  const uint32_t s_cb = sb + SM_CB, s_st = sb + SM_ST, s_xt = sb + SM_XT;
  const int cta = blockIdx.x, cid = cta >> 1, rank = cta & 1;
  const int mp = cid & 7, jn = cid >> 3;
  const int tm = mp * 2 + rank;
  const int tn2 = jn & 3, kh = jn >> 2;
  const int c0 = tn2 * 256 + kh * 128;
  if (threadIdx.x == 256) {
    asm volatile("prefetch.tensormap [%0];" ::"l"(&m_x) : "memory");
    asm volatile("prefetch.tensormap [%0];" ::"l"(&m_w1) : "memory");
    for (int s = 0; s < NST; s++) { mbar_init(bfull + s * 8, 1); mbar_init(bempty + s * 8, 16); mbar_init(bh + s * 8, 2); }
    mbar_init(bepi, 2); mbar_init(bxt, 1); mbar_init(byf, 8); mbar_init(bkf, 8); mbar_init(bdx, 1);
    for (int s = 0; s < 12; s++) mbar_init(bdep + s * 8, 1);
    if (sb & 1023) asm volatile("trap;");
    asm volatile("fence.mbarrier_init.release.cluster;" ::: "memory");
    STAMP(0);
  }
  __syncwarp();
  asm volatile("barrier.cluster.arrive.relaxed.aligned;" ::: "memory");
  if (__shfl_sync(0xffffffff, threadIdx.x >> 7, 0) == 2) {
    asm volatile("setmaxnreg.dec.sync.aligned.u32 56;");
    const int warp = (threadIdx.x >> 5) & 3, lane = threadIdx.x & 31;
    if (threadIdx.x == 256) {
      mbar_expect_tx(bfull, 16384 + B1BYTES);
      tma2d(sb, &m_x, bfull, 2 * mp * 64, tm * 128);
    }
    __syncwarp();
    asm volatile("barrier.cluster.wait.aligned;" ::: "memory");
    if (warp == 0) {
      if (lane == 0) {
        uint32_t ph = 1;
        PSTAMP(1);
#pragma unroll 1
        for (int it = 0; it < 32; it++) {
          int st = it & 3, t = it >> 4, kb = (it + 2 * mp + 12 * t) & 15;
          uint32_t a = sb + st * STAGE, b = a + 16384;
          mbar_wait(bempty + st * 8, ph);
          const bool keep = (it >> 2) == 4;
          if (it) mbar_expect_tx(bfull + st * 8, keep ? B1BYTES : 16384 + B1BYTES);
          if (it && !keep) tma2d(a, &m_x, bfull + st * 8, kb * 64, tm * 128);
          tma3d_mc(b + rank * (B1BYTES / 2), &m_w1, bfull + st * 8, 0, kb * 64 + rank * 32, (jn + 8 * t) * 7, 3);
          if (it < 4) PSTAMP(33 + it);
          if (it == XPF) asm volatile("cp.async.bulk.prefetch.L2.global [%0], 32768;" ::"l"(p.x + (size_t)(tm * 128 + jn * 16) * D_) : "memory");
          if (it == HKPF) asm volatile("cp.async.bulk.prefetch.L2.global [%0], 32768;" ::"l"(p.hk + (size_t)cta * 8 * S_) : "memory");
          if (st == 3) ph ^= 1;
        }
        mbar_wait(bdep, 0);
        fence_async();
        mbar_expect_tx(bxt, 32768);
#pragma unroll 1
        for (int st = 0; st < 4; st++) {
          mbar_wait(bempty + st * 8, ph);
          PSTAMP(66 + st);
          mbar_expect_tx(bhl + st * 8, 8192);
          mbar_expect_tx(bfull + st * 8, 2 * UCH);
#pragma unroll 1
          for (int j = 0; j < 2; j++) {
            int ch = cta * 8 + st * 2 + j;
            uint32_t dst = sb + st * STAGE + j * CHB;
            bulk_g2s(dst + CH0, p.hk + (size_t)ch * S_, 4096, bhl + st * 8);
            bulk_g2s(dst + CU0, g_U + (size_t)ch * UCH, UARR, bfull + st * 8);
            bulk_g2s(dst + CU1, g_U + (size_t)ch * UCH + UARR, UARR, bfull + st * 8);
          }
          if (st >= 2) tma2d(s_xt + (st - 2) * 16384, &m_x, bxt, c0 + (st - 2) * 64, tm * 128);
        }
        ph ^= 1;
#pragma unroll 1
        for (int it = 0; it < 32; it++) {
          int st = it & 3;
          uint32_t a = sb + st * STAGE, b = a + 16384;
          const int ix = it < 28 ? it : it - 4;
          const int k0 = (kh ^ (it >= 28)) * 896 + (it < 14 ? it * 64 : 1792 + (int)((0xDA9632C851B740ull >> (4 * (ix - 14))) & 15) * 64);
          if (it == 28) { mbar_wait(bdx, 0); fence_async(); }
          if (it == 0 || it == 14 || it == 18 || it == 22) { PSTAMP(64 + (it >> 1)); mbar_wait(bdep + (it ? (it - 6) * 2 : 8), 0); fence_async(); PSTAMP(65 + (it >> 1)); }
          mbar_wait(bempty + st * 8, ph);
          mbar_expect_tx(bfull + st * 8, it < 24 ? STAGE : 32768);
          tma2d(a, &m_act, bfull + st * 8, k0, tm * 128);
#pragma unroll 1
          for (int j = it < 24 ? rank * 2 : rank; j < (it < 24 ? rank * 2 + 2 : rank + 1); j++) tma5d_mc(b + j * 8192, &m_w2, bfull + st * 8, tn2 * 256 + ((j ^ (2 * kh)) * 64), k0 >> 5);
          if ((it >> 1) == 12) {
            if (it == 24) { mbar_wait(bdep + 40, 0); fence_async(); mbar_expect_tx(bxt, 32768); }
            tma2d(a + 32768, &m_y, bxt, tm * 128 + st * 64, c0);
          }
          if (st == 3) ph ^= 1;
        }
      }
    } else if (warp == 1) {
      const unsigned par = ld_epoch() & 1;
#pragma unroll 1
      for (int t = 0; t < 2; t++) {
        const int col = (lane >> 2) * 14 + (lane & 3) * 4;
        uint32_t bb[4];
#pragma unroll
        for (int i = 0; i < 4; i++) bb[i] = ldg32(p.b1 + (jn + 8 * t) * 224 + min(col + (i >> 1) * 112 + (i & 1) * 2, 222));
        bar_sync(NB_CS, 288);
        if (t == 0) PSTAMP(24);
#pragma unroll 1
        for (int h = 0, n = 0; h < 2; n++) {
          const float* src = g_csp + (jn + 8 * t) * 256 + (lane + 32 * h) * 4;
          uint4 v[8];
          uint32_t bad = 0;
#pragma unroll
          for (int j = 0; j < 8; j++) v[j] = ldg128_rlx(src + j * 4096);
          float4 s = make_float4(0.f, 0.f, 0.f, 0.f);
#pragma unroll
          for (int j = 0; j < 8; j++) {
            bad |= (v[j].x ^ par) | (v[j].z ^ par);
            s.x += __uint_as_float(v[j].x); s.y += __uint_as_float(v[j].y); s.z += __uint_as_float(v[j].z); s.w += __uint_as_float(v[j].w);
          }
          if (!__any_sync(0xffffffff, bad & 1)) {
            sts128(s_cb + (col + h * 112) * 8, s.x, s.y, blo(bb[0]), bhi(bb[0]));
            if ((lane & 3) != 3) sts128(s_cb + (col + h * 112) * 8 + 16, s.z, s.w, blo(bb[1]), bhi(bb[1]));
            bb[0] = bb[2]; bb[1] = bb[3];
            h++;
          }
          spin_guard(n);
        }
        __syncwarp();
        if (lane <= t) mbar_arrive(bepi);
        PSTAMP(25 + t);
      }
#pragma unroll 1
      for (int i = 0; i < 5; i++) {
        bar_sync(NB_ACT + i, 288);
        PSTAMP(80 + 2 * i);
        if (lane == 0) {
          if (i == 1) signal(C_Y + (cta >> 4), 8);
          else signal(C_ACT + (tm * 2 + kh) * 4 + (i ? i - 1 : 0), 32);
        }
        PSTAMP(81 + 2 * i);
        __syncwarp();
      }
      if (lane == 0) asm volatile("red.relaxed.gpu.global.add.u32 [%0], 1;" ::"l"(g_cnt + C_TK * 32) : "memory");
    } else {
      const unsigned ep = ld_epoch();
      const int u_ = warp - 2;
      if (u_ == 0) {
        auto ldkv = [&](int i) {
          const uint32_t bb = bkv + (i & 1) * 8, buf = s_xt + (i & 1) * 16384;
          mbar_expect_tx(bb, 16384);
          tma3d(buf, &m_k, bb, (cta & 15) * 64, (cta >> 4) * 16 + i * 4);
          tma3d(buf + 8192, &m_v, bb, (cta & 15) * 64, (cta >> 4) * 16 + i * 4);
        };
#pragma unroll 1
        for (int i = 0; i <= UWAIT + UW2; i++) {
          mbar_wait(bfull + (i & 3) * 8, (i >> 2) & 1);
          if ((i == UWAIT || i == UWAIT + UW2) && lane == 0) ldkv(i != UWAIT);
          if (i >= KVK && i < KVK + 4) {
            const size_t o = (size_t)((cta >> 4) * 256 + 128 + (i - KVK) * 32 + lane) * D_ + (cta & 15) * 64;
            asm volatile("prefetch.global.L2 [%0];" ::"l"(p.k + o) : "memory");
            asm volatile("prefetch.global.L2 [%0];" ::"l"(p.v + o) : "memory");
          }
          if (i >= W1K && i < W1K + 2) {
            const bf16* wp = p.w1 + (size_t)(((i - W1K + 2 * mp) & 15) * 64 + rank * 32 + lane) * F_ + (jn + 8) * 224;
#pragma unroll
            for (int c = 0; c < 4; c++) asm volatile("prefetch.global.L2 [%0];" ::"l"(wp + c * 64) : "memory");
          }
        }
        if (lane == 0) {
#pragma unroll 1
          for (int i = 2; i < 4; i++) { mbar_wait(i == 2 ? bkf : byf, 0); ldkv(i); }
        }
        __syncwarp();
        bar_sync(NB_U, 288);
        if (lane == 0) {
          PSTAMP(32);
          signal(C_U + (cta & 15), 16);
          PSTAMP(30);
          wait_cnt(C_U + (cta >> 3), ep);
          mbar_arrive(bdep);
        }
      } else {
        bar_sync(NB_ST, 288);
        uint2 v[4];
#pragma unroll 1
        for (int n = 0;; n++) {
          uint32_t bad = 0;
#pragma unroll
          for (int j = 0; j < 4; j++) v[j] = ldg64_rlx(g_stat + tm * 128 + (lane >> 3) * 16 + (lane & 7) + (j >> 1) * 64 + (j & 1) * 8);
#pragma unroll
          for (int j = 0; j < 4; j++) bad |= v[j].x ^ ep;
          if (!__any_sync(0xffffffff, bad & 0xffff)) break;
          spin_guard(n);
        }
#pragma unroll
        for (int j = 0; j < 4; j += 2) sts128u(s_st + lane * 16 + j * 256, (v[j].x & 0xffff0000u) ^ 0x80000000u, v[j].y, (v[j + 1].x & 0xffff0000u) ^ 0x80000000u, v[j + 1].y);
        __syncwarp();
        if (lane == 0) mbar_arrive(bepi);
        PSTAMP(27);
      }
      __syncwarp();
      const uint32_t dv = ldg16(p.Dv + cta * 8 + (lane & 3) * 2 + u_, 1) * 0x10001;
#pragma unroll 1
      for (int i = 0; i < 8; i++) {
        const uint32_t hs = sb + (i >> 1) * STAGE + u_ * CHB + CH0 + (i & 1) * 2048 + lane * 16;
        if (!(i & 1)) mbar_wait(bhl + (i >> 1) * 8, 0);
        float4 v[4];
        uint32_t pv[4];
#pragma unroll
        for (int j = 0; j < 4; j++) { v[j] = lds128(hs + j * 512); pv[j] = lds32(hs + j * 512 - 4); }
        if (!((i & 1) | lane)) pv[0] = 0;
#pragma unroll
        for (int j = 0; j < 4; j++) {
          const uint32_t x = __float_as_uint(v[j].x), y = __float_as_uint(v[j].y), z = __float_as_uint(v[j].z), w = __float_as_uint(v[j].w);
          sts128u(hs + (CH1 - CH0) + j * 512, __byte_perm(pv[j], x, 0x5432), __byte_perm(x, y, 0x5432), __byte_perm(y, z, 0x5432), __byte_perm(z, w, 0x5432));
        }
        if (lane * 2 == i) asm volatile("st.shared.b32 [%0], %1;" ::"r"(sb + lane * STAGE + u_ * CHB), "r"(dv) : "memory");
        if (i & 1) { __syncwarp(); if (lane == 0) mbar_arrive(bh + (i >> 1) * 8); PSTAMP(52 + (i >> 1)); }
        if (i == 0) PSTAMP(56);
      }
      if (lane == 0) {
        if (u_ == 0) {
#pragma unroll 1
          for (int i = 0; i < 4; i++) { wait_cnt(C_ACT + (tm * 2 + kh) * 4 + i, ep); mbar_arrive(bdep + 8 + i * 8); }
          wait_cnt(C_ACT + (tm * 2 + (kh ^ 1)) * 4 + 3, ep);
          mbar_arrive(bdx);
        } else {
          wait_cnt(C_Y + (c0 >> 7), ep);
          mbar_arrive(bdep + 40);
        }
      }
    }
  } else {
    asm volatile("setmaxnreg.inc.sync.aligned.u32 224;");
    const uint32_t e0 = mapa(bempty, 0), e1 = mapa(bempty, 1);
    uint32_t hp[56];
    asm volatile("barrier.cluster.wait.aligned;" ::: "memory");
    {
      float d[112];
#pragma unroll 1
      for (uint32_t t = 0; t < 2; t++) {
      LOCALS;
      uint2 sw = make_uint2(0, 0);
      uint32_t c0_ = 0, c1_ = 0;
      const int wu = WGU;
      const uint32_t da0 = mkdesc(sb, 16) + wu * 512, db0 = mkdesc(sb + 16384, 2048);
      auto kstep = [&](uint32_t kb) {
        const uint32_t st = kb & 3, so = st * (STAGE >> 4);
        mbar_wait(bfull + st * 8, (kb >> 2) & 1);
        wg_fence();
#pragma unroll
        for (int kk = 0; kk < 4; kk++) {
          mma_n224(d, da0 + (so + kk * 2), db0 + (so + (((kk & 1) * 1024 + (kk >> 1) * (B1BYTES / 2)) >> 4)), kk || kb);
          if (kk == SPL1) {
            wg_commit();
            wg_wait<1>();
            if (kb && lane == 0) { mbar_arrive_remote(e0 + ((kb - 1) & 3) * 8); mbar_arrive_remote(e1 + ((kb - 1) & 3) * 8); }
            if (kk < 3) wg_fence();
          }
        }
        if (SPL1 < 3) wg_commit();
      };
      const int W = rank * 56 + (wg * 4 + w) * 7 + min(lane & 7, 6), hf = lane >> 4;
      const uint32_t csb = sb + 16384 + hf * (B1BYTES / 2) + (W >> 4) * 2048 + ((lane >> 3) & 1) * 64 + (W & 3) * 4;
      auto cs_ld = [&](uint32_t kb, int r) { return lds32(csb + kb * STAGE + (r & 12) * 128 + (((r ^ (hf * 2)) & 3) * 128 + ((((W >> 2) ^ r ^ (hf * 2)) & 3) << 4))); };
      auto cs_pub = [&](float cs0, float cs1, int t, uint32_t par) {
        cs0 += __shfl_xor_sync(0xffffffff, cs0, 8); cs1 += __shfl_xor_sync(0xffffffff, cs1, 8);
        cs0 += __shfl_xor_sync(0xffffffff, cs0, 16); cs1 += __shfl_xor_sync(0xffffffff, cs1, 16);
        if (lane < 8) stg64_rlx(g_csp + mp * 4096 + (jn + 8 * t) * 256 + (rank * 8 + wg * 4 + w) * 16 + lane * 2, (__float_as_uint(cs0) & ~1u) | par, __float_as_uint(cs1));
        bar_arrive(NB_CS, 288);
      };
      const int uch = (cta & 15) * 64 + (wg * 4 + w) * 8 + g, uT = (cta >> 4) * 256;
      const int rs_ = 4 * ((lane & 1) ^ 1) + 3 - ((lane >> 1) & 3);
      const uint32_t ma = s_xt + ((lane >> 3) * 8 + rs_) * 128 + ((rs_ ^ (wg * 4 + w)) << 4);
      uint8_t* ub = g_U + (size_t)uch * UCH + (124 - (uT >> 4) + q) * 16;
      auto ustep = [&](uint32_t i, auto&& mid) {
        uint32_t Q[10], V[8];
        const uint32_t la = ma + (i & 1) * 16384;
        mbar_wait(bkv + (i & 1) * 8, i >> 1);
        ldsm4t(Q + 6, la + 4096); ldsm4t(Q + 2, la); ldsm4t(V, la + 8192); ldsm4t(V + 4, la + 12288);
        mid();
        const uint32_t n0 = __shfl_sync(0xffffffff, Q[8], (lane & 28) | ((lane + 1) & 3)), n1 = __shfl_sync(0xffffffff, Q[9], (lane & 28) | ((lane + 1) & 3));
        asm volatile("" ::"r"(Q[2]), "r"(V[0]), "r"(V[4]) : "memory");
        __syncwarp();
        if (lane == 0 && i < 2) mbar_arrive(i ? byf : bkf);
        const uint32_t w0 = __byte_perm(sw.x, 0, 0x1010), w1 = __byte_perm(sw.x, 0, 0x3232), w2 = __byte_perm(sw.y, 0, 0x1010), w3 = __byte_perm(sw.y, 0, 0x3232);
        Q[0] = q == 3 ? c0_ : n0; Q[1] = q == 3 ? c1_ : n1;
        c0_ = n0; c1_ = n1;
        uint32_t pm = __byte_perm(Q[9], Q[8], 0x5432);
#pragma unroll
        for (int j = 7; j >= 0; j--) {
          const uint32_t pc = __byte_perm(Q[j + 1], Q[j], 0x5432);
          V[j] = hmul2(hfma2(Q[j + 2], w0, hfma2(pm, w1, hfma2(Q[j + 1], w2, hmul2(pc, w3)))), V[j]);
          pm = pc;
          if (j == 4) stg128(ub - i * 64, V[7], V[6], V[5], V[4]);
        }
        stg128(ub + UARR - i * 64, V[3], V[2], V[1], V[0]);
      };
        if (t == 0) {
          uint32_t c2_, lt = tid;
          asm volatile("" : "+r"(lt));
          const unsigned ep = ld_epoch();
          {
            const int srow = tm * 128 + jn * 16 + (lt >> 4);
            const uint4* xp = (const uint4*)(p.x + (size_t)srow * D_) + (lt & 15);
            uint4 xv[8];
            float f[64], a[4] = {0.f, 0.f, 0.f, 0.f}, cs0 = 0.f, cs1 = 0.f;
#pragma unroll
            for (int kb = 0; kb < 2; kb++) {
              uint32_t v[16];
              mbar_wait(bfull + kb * 8, 0);
#pragma unroll
              for (int r = 0; r < 16; r++) v[r] = cs_ld(kb, r);
              kstep(kb);
              if (kb == 0) STAMP(4 + wg);
              if (kb == 1) STAMP0(96);
#pragma unroll
              for (int i = 4 * kb; i < 4 * kb + 4; i++) xv[i] = ldg128(xp + i * 16);
#pragma unroll
              for (int r = 0; r < 16; r++) { cs0 += blo(v[r]); cs1 += bhi(v[r]); }
              asm volatile("" : "+f"(cs0), "+f"(cs1));
            }
            kstep(2);
            STAMP0(97);
            cs_pub(cs0, cs1, 0, ep & 1);
            asm volatile("st.shared.b32 [%0], %1;" ::"r"(s_par), "r"(ep & 1) : "memory");
            *(uint2*)(g_U + (size_t)((cta & 15) * 64 + (cta >> 4) * 8) * UCH + (lt >> 4) * UARR + 2048 + (lt & 15) * 8) = make_uint2(0, 0);
#pragma unroll
            for (int h = 0; h < 2; h++) {
              kstep(3 + h);
              STAMP0(98 + h);
#pragma unroll
              for (int i = 4 * h; i < 4 * h + 4; i++) {
                asm volatile("" : "+r"(xv[i].x), "+r"(xv[i].y), "+r"(xv[i].z), "+r"(xv[i].w));
                const uint32_t e[4] = {xv[i].x, xv[i].y, xv[i].z, xv[i].w};
#pragma unroll
                for (int c = 0; c < 4; c++) { f[8 * i + 2 * c] = blo(e[c]); f[8 * i + 2 * c + 1] = bhi(e[c]); a[c] += f[8 * i + 2 * c] + f[8 * i + 2 * c + 1]; }
              }
              asm volatile("" : "+f"(a[0]), "+f"(a[1]), "+f"(a[2]), "+f"(a[3]));
            }
            kstep(5);
            STAMP0(100);
            float m = (a[0] + a[1]) + (a[2] + a[3]);
#pragma unroll
            for (int o = 1; o < 16; o *= 2) m += __shfl_xor_sync(0xffffffff, m, o);
            m *= 1.f / D_;
            asm volatile("" : "+f"(m));
            {
              const int lch = (cta & 15) * 64 + (lt >> 2);
              const bf16* kp = p.k + (size_t)uT * D_ + lch;
              sw = ldg64(p.shk + lch * 4);
              c0_ = ldg16(kp - 3 * D_, uT); c1_ = ldg16(kp - D_, uT); c2_ = ldg16(kp - 2 * D_, uT);
            }
            kstep(6);
            STAMP0(101);
            asm volatile("" : "+f"(m));
            a[0] = a[1] = a[2] = a[3] = 0.f;
#pragma unroll
            for (int i = 0; i < 64; i++) { float c = f[i] - m; a[i & 3] = fmaf(c, c, a[i & 3]); }
            float var = (a[0] + a[1]) + (a[2] + a[3]), sq;
            asm volatile("" : "+f"(var));
            kstep(7);
            STAMP0(102);
#pragma unroll
            for (int o = 1; o < 16; o *= 2) var += __shfl_xor_sync(0xffffffff, var, o);
            asm("sqrt.approx.ftz.f32 %0, %1;" : "=f"(sq) : "f"(rbf(rbf(var * (1.f / D_)) + 1e-5f)));
            if (!(lane & 15)) stg128_rlx(g_stat + srow, __float_as_uint(rbf(m)) | (ep & 0xffff), __float_as_uint(rcp(rbf(sq))), 0, 0);
            bar_arrive(NB_ST, 288);
          }
#pragma unroll 1
          for (uint32_t kb = 8, i = 0; kb < 16; kb++) {
            if ((PRI & 1) && kb == PRK && wu == 1) bar_sync(NB_PRI, 256);
            if ((UMASK >> kb) & 1) {
              if (i == 0) { asm volatile("" : "+r"(c2_)); c1_ |= c2_ << 16; }
              ustep(i, [&]() { kstep(kb); });
              i++;
            } else kstep(kb);
            STAMP0(95 + kb);
          }
          if ((PRI & 1) && wu == 0) bar_arrive(NB_PRI, 256);
          bar_arrive(NB_U, 288);
        } else {
          float cs0 = 0.f, cs1 = 0.f;
#pragma unroll 1
          for (uint32_t kb = 0; kb < 2; kb++) {
            uint32_t v[16];
            mbar_wait(bfull + kb * 8, 0);
#pragma unroll
            for (int r = 0; r < 16; r++) v[r] = cs_ld(kb, r);
            kstep(kb);
#pragma unroll
            for (int r = 0; r < 16; r++) { cs0 += blo(v[r]); cs1 += bhi(v[r]); }
            STAMP0(90 + kb);
          }
          cs_pub(cs0, cs1, 1, lds32(s_par));
          bf16 *pa = g_act + (size_t)(tm * 128 + wg * 64 + w * 16 + g) * F_ + jn * 224 + q * 8, *pb = pa + 8 * F_;
#pragma unroll 1
          for (uint32_t i = 0; i < 2; i++) {
#pragma unroll
            for (int s = 0; s < 7; s++) {
              if ((PRI & 2) && s == PRK - 9 && i + wu == 2) bar_sync(NB_PRI, 256);
              kstep(2 + i * 7 + s);
              if ((PRI & 2) && s == 6 && i > wu) bar_arrive(NB_PRI, 256);
              act_chunk(hp + 4 * s, ((s & 1) ? pb : pa) + (s >> 1) * 32);
            }
#pragma unroll
            for (int s = 0; s < 28; s++) hp[s] = hp[s + 28];
            bf16* tp = pa; pa = pb + 96; pb = tp + 128;
          }
          bar_arrive(NB_ACT, 288);
        }
        wg_wait<0>();
        if (lane == 0) { mbar_arrive_remote(e0 + 24); mbar_arrive_remote(e1 + 24); }
        if (t + wu == 2) bar_arrive(NB_ORD0, 256);
        STAMP(6 + 4 * t + wg);
        mbar_wait(bepi, t);
        {
        LOCALS;
        const float4 st = lds128(s_st + (wg * 32 + w * 8 + g) * 16);
        const float nm0 = st.x, rs0 = st.y, nm1 = st.z, rs1 = st.w;
#pragma unroll
        for (int j = 0; j < 28; j++) {
          float4 cb = lds128(s_cb + j * 64 + q * 16);
          hp[(j >> 2) * 8 + (j & 3)] = pack2(fmaf(fmaf(nm0, cb.x, d[4 * j]), rs0, cb.z), fmaf(fmaf(nm0, cb.y, d[4 * j + 1]), rs0, cb.w));
          hp[(j >> 2) * 8 + 4 + (j & 3)] = pack2(fmaf(fmaf(nm1, cb.x, d[4 * j + 2]), rs1, cb.z), fmaf(fmaf(nm1, cb.y, d[4 * j + 3]), rs1, cb.w));
        }
        STAMP(8 + 4 * t + wg);
        }
      }
    }
    {
      LOCALS;
      float d[64];
      uint32_t xa[16], xb[16], xc[16], xd[16];
      const uint32_t uoff = ((g & 1) ? CU0 : CU1) + (120 - 8 * w + 2 * (g >> 1)) * 16 + 12 - 4 * q;
      const uint32_t hoff = ((g & 1) ? CH0 : CH1) + (64 * w + (g >> 1) + q - 7) * 4;
      const int wu = WGU;
      const uint32_t zr = p.zero, dbs0 = mkdesc(sb + CU0, CU1 - CU0) + wu * (CHB >> 4);
      const uint32_t xb_w = sb + (2 + wg) * STAGE + XOFF + lane * 8 + w * 3072;
      uint32_t xr_[3];
#pragma unroll
      for (int dw = 1; dw < 4; dw++) xr_[dw - 1] = xb_w + (w + dw > 3 ? -13056 : 0) + dw * 3072 + (2 + dw) * 256;
      auto xsts = [&](int c) {
#pragma unroll
        for (int i = 0; i < 3; i++)
          if (c || i >= w) sts64(xb_w + (c * 3 + i) * 256, pack2(d[16 * c + 4 * i], d[16 * c + 4 * i + 1]), pack2(d[16 * c + 4 * i + 2], d[16 * c + 4 * i + 3]));
      };
      uint32_t ub = sb + wg * CHB;
      mbar_wait(bh, 0);
      mbar_wait(bfull, 0);
      loadA<0>(xa, ub + hoff); loadA<1>(xb, ub + hoff);
#pragma unroll 1
      for (int it = 0; it < 4; it++) {
        const uint32_t hb = ub + hoff, dbs = dbs0 + it * (STAGE >> 4);
        dupA(xa, zr);
        CSTAMP(0);
        if (HOFF == 9 && it) bar_sync(NB_WG0 + wu, 128);
        else bar_sync(NB_ORD0 + wu, 256);
        CSTAMP(1);
        dupA(xb, zr);
        mmaG<0>(d, xa, dbs);
        loadA<2>(xc, hb); mmaG<1>(d, xb, dbs); dupA(xc, zr);
        loadA<3>(xd, hb);
        wg_wait<1>(); loadA<4>(xa, hb); mmaG<2>(d, xc, dbs); dupA(xd, zr); dupA(xa, zr);
        wg_wait<1>(); loadA<5>(xb, hb); mmaG<3>(d, xd, dbs); dupA(xb, zr); xsts(3);
        if (HOFF == 9 && it + wu == 0) bar_arrive(NB_ORD1, 256);
        if (HOFF == 3 && !(it == 3 && wu == 1)) bar_arrive(NB_ORD0 + (wu ^ 1), 256);
        wg_wait<1>(); loadA<6>(xc, hb); mmaG<4>(d, xa, dbs); mmaG<5>(d, xb, dbs); dupA(xc, zr);
        wg_wait<2>(); loadA<7>(xd, hb);
        if (HOFF == 0 && !(it == 3 && wu == 1)) bar_arrive(NB_ORD0 + (wu ^ 1), 256);
        mmaG<6>(d, xc, dbs); dupA(xd, zr);
        if (HOFF == 1 && !(it == 3 && wu == 1)) bar_arrive(NB_ORD0 + (wu ^ 1), 256);
        mmaG<7>(d, xd, dbs);
        if (HOFF == 2 && !(it == 3 && wu == 1)) bar_arrive(NB_ORD0 + (wu ^ 1), 256);
        CSTAMP(2);
        xsts(2);
        uint32_t uu[8];
#pragma unroll
        for (int a = 0; a < 4; a++)
#pragma unroll
          for (int hh = 0; hh < 2; hh++) uu[2 * a + hh] = lds32(ub + uoff - a * 512 + hh * 16);
        const uint32_t dval = lds32(ub);
        bf16* yp = g_Y + (size_t)(cta * 8 + it * 2 + wg) * S_ + 128 * w + 112 - 32 * (g >> 1) + 8 * (g & 1) + 2 * q;
        auto yout = [&](int a0, int a1) {
          uint2 t[12];
#pragma unroll
          for (int dw = 1; dw < 4; dw++) {
            if (a0 == 0) t[dw - 1] = lds64p<9 * 256>(xr_[dw - 1], w + dw > 3);
            if (a0 <= 1 && a1 > 1) t[dw + 2] = lds64p<6 * 256>(xr_[dw - 1], true);
            if (a0 <= 2 && a1 > 2) t[dw + 5] = lds64p<3 * 256>(xr_[dw - 1], true);
            if (a1 > 3) t[dw + 8] = lds64p<0>(xr_[dw - 1], true);
          }
#pragma unroll
          for (int a = a0; a < a1; a++) {
            float s0 = d[60 - 16 * a], s1 = d[61 - 16 * a], s2 = d[62 - 16 * a], s3 = d[63 - 16 * a];
#pragma unroll
            for (int i = 3 * a; i < 3 * a + 3; i++) { s0 += blo(t[i].x); s1 += bhi(t[i].x); s2 += blo(t[i].y); s3 += bhi(t[i].y); }
#pragma unroll
            for (int hh = 0; hh < 2; hh++)
              *(uint32_t*)(yp + 512 * a - 16 * hh) = hadd2(movm(pack2(hh ? s1 : s0, hh ? s3 : s2)), hmul2(__byte_perm(uu[2 * a + hh], 0, 0x1032), dval));
          }
        };
        if (it < 3) { ub += STAGE; mbar_wait(bh + it * 8 + 8, 0); mbar_wait(bfull + it * 8 + 8, 0); }
        wg_wait<2>();
        xsts(1);
        bar_sync(NB_WG0 + wu, 128);
        CSTAMP(4);
        yout(0, 3);
        CSTAMP(5);
        wg_wait<0>();
        CSTAMP(6);
        xsts(0);
        asm volatile("" ::"r"(dval), "r"(uu[0]), "r"(uu[1]), "r"(uu[2]), "r"(uu[3]), "r"(uu[4]), "r"(uu[5]), "r"(uu[6]), "r"(uu[7]) : "memory");
        __syncwarp();
        if (lane == 0 && it < 3 && it != 2 + wg) { mbar_arrive_remote(e0 + it * 8); mbar_arrive_remote(e1 + it * 8); }
        loadA<0>(xa, ub + hoff); loadA<1>(xb, ub + hoff);
        bar_sync(NB_WG0 + wu, 128);
        CSTAMP(3);
        yout(SHAD == 2 ? 3 : 0, 4);
      }
      bar_arrive(NB_Y, 288);
      asm volatile("" ::"r"(xa[0]), "r"(xb[15]) : "memory");
      __syncwarp();
      if (lane == 0) {
        mbar_arrive_remote(e0 + 24); mbar_arrive_remote(e1 + 24);
        if (wg == 0) { mbar_arrive_remote(e0 + 16); mbar_arrive_remote(e1 + 16); }
      }
    }
    {
      LOCALS;
      STAMP(14 + wg);
      float d[128];
      const uint32_t da0 = mkdesc(sb, 16) + WGU * 512, db0 = mkdesc(sb + 16384, 8192);
      auto kstep = [&](uint32_t kb) {
        const uint32_t st = kb & 3, so = st * (STAGE >> 4);
        mbar_wait(bfull + st * 8, ((kb >> 2) & 1) ^ 1);
        wg_fence();
#pragma unroll
        for (int kk = 0; kk < 4; kk++) {
          mma_n256(d, da0 + (so + kk * 2), db0 + (so + kk * 128), kk || kb);
          if (kk == SPL2) {
            wg_commit();
            wg_wait<1>();
            if (kb && lane == 0) { mbar_arrive_remote(e0 + ((kb - 1) & 3) * 8); mbar_arrive_remote(e1 + ((kb - 1) & 3) * 8); }
            if (kk < 3) wg_fence();
          }
        }
        if (SPL2 < 3) wg_commit();
      };
      {
        bf16 *pa = g_act + (size_t)(tm * 128 + wg * 64 + w * 16 + g) * F_ + (jn + 8) * 224 + q * 8, *pb = pa + 8 * F_;
#pragma unroll 1
        for (uint32_t i = 0; i < 2; i++) {
#pragma unroll
          for (int s = 0; s < 7; s++) {
            kstep(i * 7 + s);
            act_chunk(hp + 4 * s, ((s & 1) ? pb : pa) + (s >> 1) * 32);
            if (s == 5 && i == 0) bar_arrive(NB_ACT + 2, 288);
            if (s == 2 && i == 1) bar_arrive(NB_ACT + 3, 288);
          }
#pragma unroll
          for (int s = 0; s < 28; s++) hp[s] = hp[s + 28];
          bf16* tp = pa; pa = pb + 96; pb = tp + 128;
          STAMP(40 + 2 * i + wg);
        }
        bar_arrive(NB_ACT + 4, 288);
      }
      mbar_wait(bxt, 0);
#pragma unroll 1
      for (uint32_t kb = 14; kb < 24; kb++) {
        kstep(kb);
        if (kb == 19) STAMP(44 + wg);
      }
      const int mr = lane & 7, mi = lane >> 3;
      uint32_t sr[32];
      const uint32_t xrow = s_xt + (wg * 64 + w * 16 + (mi & 1) * 8 + mr) * 128;
      const uint32_t yrow = sb + wg * STAGE + 32768 + ((mi >> 1) * 8 + mr) * 128 + (((w * 2 + (mi & 1)) ^ mr) << 4);
      const float4 st = lds128(s_st + (wg * 32 + w * 8 + g) * 16);
      const uint32_t par = lds32(s_par);
      wg_wait<0>();
      STAMP(46 + wg);
      if (lane == 0) { mbar_arrive_remote(e0 + 24); mbar_arrive_remote(e1 + 24); }
      uint32_t pk[32];
#pragma unroll
      for (int i = 0; i < 32; i++) { pk[i] = pack2(d[64 + 2 * i], d[65 + 2 * i]); asm volatile("" : "+r"(pk[i])); }
      uint4 r[8];
      const uint4* src = g_xch + (cta ^ PARTX) * 2048 + tid;
#pragma unroll
      for (int s = 0; s < 8; s++) {
        const uint32_t so = (s & 3) * (STAGE >> 4);
        if (s == RLD) {
          STAMP(48 + wg);
#pragma unroll
          for (int j = 0; j < 8; j++) r[j] = ldg128_rlx(src + j * 256);
        }
        mbar_wait(bfull + (s & 3) * 8, s < 4);
        wg_fence();
#pragma unroll
        for (int kk = 0; kk < 4; kk++) {
          mma_n128(d, da0 + (so + kk * 2), db0 + (so + kk * 128), 1);
          if (kk == 0 && s >= 1 && s <= 4) {
            wg_commit();
            wg_wait<1>();
            if (lane == 0) { mbar_arrive_remote(e0 + (s - 1) * 8); mbar_arrive_remote(e1 + (s - 1) * 8); }
            wg_fence();
          }
        }
        wg_commit();
        if (s == 0) {
          uint4* dst = g_xch + cta * 2048 + tid;
#pragma unroll
          for (int j = 0; j < 8; j++) stg128_rlx(dst + j * 256, (pk[4 * j] & ~1u) | par, pk[4 * j + 1], pk[4 * j + 2], pk[4 * j + 3]);
          STAMP(22 + wg);
        }
        if (s >= SRS && s < SRS + 4) {
          if (s == SRS) mbar_wait(bxt, 1);
          const uint32_t nm[2] = {pack2(st.x, st.x), pack2(st.z, st.z)};
          const float rs[2] = {st.y, st.w};
#pragma unroll
          for (int jp = 2 * (s - SRS); jp < 2 * (s - SRS) + 2; jp++) {
            uint32_t xr[4], xa = xrow + (jp >> 2) * 16384 + ((((jp & 3) * 2 + (mi >> 1)) ^ mr) << 4);
            ldsm4t(sr + 4 * jp, yrow + jp * 2048);
            asm volatile("ldmatrix.sync.aligned.m8n8.x4.shared.b16 {%0,%1,%2,%3}, [%4];" : "=r"(xr[0]), "=r"(xr[1]), "=r"(xr[2]), "=r"(xr[3]) : "r"(xa) : "memory");
#pragma unroll
            for (int m = 0; m < 4; m++) {
              uint32_t xc = hadd2(xr[m], nm[m & 1]);
              sr[4 * jp + m] = hmul2(pack2(blo(xc) * rs[m & 1], bhi(xc) * rs[m & 1]), sr[4 * jp + m]);
              asm volatile("" : "+r"(sr[4 * jp + m]));
            }
          }
        }
      }
      STAMP(16 + wg);
#pragma unroll 1
      for (int n = 0; n < SPINMAX; n++) {
        uint32_t bad = 0;
#pragma unroll
        for (int j = 0; j < 8; j++) bad |= r[j].x ^ par;
        if (!__any_sync(0xffffffff, bad & 1)) break;
#pragma unroll
        for (int j = 0; j < 8; j++) r[j] = ldg128_rlx(src + j * 256);
      }
      float rf[64];
#pragma unroll
      for (int j = 0; j < 8; j++) {
        const uint32_t e[4] = {r[j].x, r[j].y, r[j].z, r[j].w};
#pragma unroll
        for (int c = 0; c < 4; c++) {
          rf[8 * j + 2 * c] = blo(e[c]) * -LOG2E; rf[8 * j + 2 * c + 1] = bhi(e[c]) * -LOG2E;
          asm volatile("" : "+f"(rf[8 * j + 2 * c]), "+f"(rf[8 * j + 2 * c + 1]));
        }
      }
      STAMP(50 + wg);
      wg_wait<0>();
      STAMP(18 + wg);
#pragma unroll
      for (int jp = 0; jp < 8; jp++) {
        uint32_t o[4], xr[4], xa = xrow + (jp >> 2) * 16384 + ((((jp & 3) * 2 + (mi >> 1)) ^ mr) << 4);
        asm volatile("ldmatrix.sync.aligned.m8n8.x4.shared.b16 {%0,%1,%2,%3}, [%4];" : "=r"(xr[0]), "=r"(xr[1]), "=r"(xr[2]), "=r"(xr[3]) : "r"(xa) : "memory");
#pragma unroll
        for (int c = 0; c < 2; c++) {
          int j = jp * 2 + c;
          float z[4];
#pragma unroll
          for (int i = 0; i < 4; i++) z[i] = fmaf(d[4 * j + i], -LOG2E, rf[4 * j + i]);
          silu4(z);
#pragma unroll
          for (int hh = 0; hh < 2; hh++) {
            int m = c * 2 + hh;
            o[m] = hfma2(sr[4 * jp + m], pack2(z[2 * hh], z[2 * hh + 1]), xr[m]);
          }
        }
        asm volatile("stmatrix.sync.aligned.m8n8.x4.shared.b16 [%0], {%1,%2,%3,%4};" ::"r"(xa), "r"(o[0]), "r"(o[1]), "r"(o[2]), "r"(o[3]) : "memory");
        if (jp == 3 || jp == 7) {
          asm volatile("fence.proxy.async.shared::cta;" ::: "memory");
          __syncwarp();
          if (lane == 0) {
            tma2d_store(&m_out, s_xt + (jp >> 2) * 16384 + (wg * 64 + w * 16) * 128, c0 + (jp >> 2) * 64, tm * 128 + wg * 64 + w * 16);
            asm volatile("cp.async.bulk.commit_group;" ::: "memory");
          }
        }
      }
      if (lane == 0) asm volatile("cp.async.bulk.wait_group.read 0;" ::: "memory");
      STAMP(20 + wg);
    }
  }
}

typedef CUresult (*EncFn)(CUtensorMap*, CUtensorMapDataType, cuuint32_t, void*, const cuuint64_t*, const cuuint64_t*, const cuuint32_t*, const cuuint32_t*,
                          CUtensorMapInterleave, CUtensorMapSwizzle, CUtensorMapL2promotion, CUtensorMapFloatOOBfill);
static CUtensorMap mkmap(EncFn enc, const void* ptr, int rank, const uint64_t* dims, const uint64_t* strides, const uint32_t* box, CUtensorMapSwizzle sw) {
  CUtensorMap m;
  uint32_t es[5] = {1, 1, 1, 1, 1};
  enc(&m, CU_TENSOR_MAP_DATA_TYPE_BFLOAT16, rank, (void*)ptr, (const cuuint64_t*)dims, (const cuuint64_t*)strides, box, es, CU_TENSOR_MAP_INTERLEAVE_NONE, sw,
      CU_TENSOR_MAP_L2_PROMOTION_L2_256B, CU_TENSOR_MAP_FLOAT_OOB_FILL_NONE);
  return m;
}

extern "C" void kernel_launch(void* const* d_in, const int* in_sizes, int n_in, void* d_out, int out_size) {
  void* fn = nullptr;
  cudaDriverEntryPointQueryResult qr;
  cudaGetDriverEntryPoint("cuTensorMapEncodeTiled", &fn, cudaEnableDefault, &qr);
  EncFn enc = (EncFn)fn;
  void *act, *Y;
  cudaGetSymbolAddress(&act, g_act); cudaGetSymbolAddress(&Y, g_Y);
  uint64_t dx[2] = {D_, S_}, sx[1] = {D_ * 2};
  uint32_t b128[2] = {64, 128}, b16[2] = {64, 16};
  CUtensorMap m_x = mkmap(enc, d_in[0], 2, dx, sx, b128, CU_TENSOR_MAP_SWIZZLE_128B);
  CUtensorMap m_out = mkmap(enc, d_out, 2, dx, sx, b16, CU_TENSOR_MAP_SWIZZLE_128B);
  uint64_t dw1[3] = {32, D_, F_ / 32}, sw1[2] = {F_ * 2, 64};
  uint32_t bw1[3] = {32, 32, 7};
  CUtensorMap m_w1 = mkmap(enc, d_in[7], 3, dw1, sw1, bw1, CU_TENSOR_MAP_SWIZZLE_64B);
  uint64_t da[2] = {F_, S_}, sa[1] = {F_ * 2};
  CUtensorMap m_act = mkmap(enc, act, 2, da, sa, b128, CU_TENSOR_MAP_SWIZZLE_128B);
  uint64_t dw2[5] = {D_, 2, 4, 4, F_ / 32}, sw2[4] = {D_ * 2, 8 * D_ * 2, 2 * D_ * 2, 32 * D_ * 2};
  uint32_t bw2[5] = {64, 2, 4, 4, 2};
  CUtensorMap m_w2 = mkmap(enc, d_in[9], 5, dw2, sw2, bw2, CU_TENSOR_MAP_SWIZZLE_128B);
  uint64_t dy[2] = {S_, D_}, sy[1] = {S_ * 2};
  CUtensorMap m_y = mkmap(enc, Y, 2, dy, sy, b128, CU_TENSOR_MAP_SWIZZLE_128B);
  uint64_t dk[3] = {D_, S_ / 16, 16}, sk[2] = {16 * D_ * 2, D_ * 2};
  uint32_t bkv[3] = {64, 4, 16};
  CUtensorMap m_k = mkmap(enc, d_in[1], 3, dk, sk, bkv, CU_TENSOR_MAP_SWIZZLE_128B);
  CUtensorMap m_v = mkmap(enc, d_in[2], 3, dk, sk, bkv, CU_TENSOR_MAP_SWIZZLE_128B);
  Params p;
  p.x = (const bf16*)d_in[0]; p.k = (const bf16*)d_in[1]; p.v = (const bf16*)d_in[2]; p.shk = (const bf16*)d_in[3];
  p.hk = (const bf16*)d_in[4]; p.Dv = (const bf16*)d_in[5]; p.b1 = (const bf16*)d_in[8]; p.w1 = (const bf16*)d_in[7]; p.zero = 0;
  cudaFuncSetAttribute(fused_kernel, cudaFuncAttributeMaxDynamicSharedMemorySize, SMEM_BYTES);
  fused_kernel<<<128, 384, SMEM_BYTES, cudaStreamPerThread>>>(m_x, m_w1, m_act, m_w2, m_y, m_out, m_k, m_v, p);
}
```

```cpp
#include <cuda_runtime.h>
#include <cuda.h>
#include <cuda_bf16.h>
#include <stdint.h>

typedef __nv_bfloat16 bf16;
typedef __nv_bfloat162 bf162;
constexpr int S_ = 2048, D_ = 1024, F_ = 3584;
constexpr int UARR = 2176, UCH = 2 * UARR;
constexpr int CU0 = 64, CH0 = CU0 + UARR, CU1 = CH0 + 4096 + 64, CH1 = CU1 + UARR, CHB = CH1 + 4096;
constexpr int STAGE = 49152, NST = 4;
constexpr int XOFF = 2 * CHB;
constexpr int SM_XT = NST * STAGE;
constexpr int SM_ST = SM_XT + 32768;
constexpr int SM_CB = SM_ST + 512;
constexpr int SM_BARS = SM_CB + 2048 + 64;
constexpr int SMEM_BYTES = SM_BARS + 256;

__device__ __align__(1024) uint4 g_stat[S_];
__device__ __align__(1024) float g_csp[4 * 8 * 512];
__device__ __align__(1024) bf16 g_act[S_ * F_];
__device__ __align__(1024) uint8_t g_U[(size_t)D_ * UCH];
__device__ __align__(1024) bf16 g_Y[D_ * S_];
__device__ __align__(1024) uint4 g_xch[128 * 8 * 256];
enum { C_U = 0, C_ACT = 16, C_Y = 144, C_TK = 152 };
__device__ unsigned g_cnt[(C_TK + 1) * 32];
#define CSTAMP(k)
#define STAMP(i)
#define STAMP0(i)
#define PSTAMP(i)

#define UITER 16
#define MAPM 1
#define RLD (2 * TL - 1)
#define UWAIT 5
#define NOCS 0
#define PRE0 0
#define PRE1 1
#define WF 1
#define VU 1
#define M1R 1
#define LD2 2
#define XH 2
#define UO 0
#define HS 1
#define ORDF 0
#define EARLY 0
#define HLG 1
#define SHW 1
#define RC 216
#define PL 0
#define W2P 14
#define PK2 0
#define PKH 4
#define XS 0
#define XN 2
#define EPM 1
#define EPZ 0
#define EPS 0
#define EPSB "4"
#define SCL 1
#define EPW 1
#define EPO 1
#define UMASK 0x6600
#define HKL 0
#define UW2 2
#define KVK 20
#define W1K 40
#define HKPF 40
#define XPF 40
#define SPL1 3
#define SPL2 0
#define BIGN 1
#define SIL 4
#define RFPIN 1
#define DCPY 0
#define MISH 1
#define XB16 1
#define HOFF 0
#define PRI 2
#define PRK 14
#define FDUP 1
#define SHAD 0
#define SRS 1
#define PF0 1
#define PERT 2
#define UMASK1 UMASK
#define CSK 0
#define T1UN 1
constexpr int T1U = T1UN;
#define SPL0 0
#define BRK 1
#define NODR 1
#define TL 4
#define SRN 2
constexpr int NF = 28 - TL;
#define PT 6
#define PTW 0
#define RL0 0
#define KS 8
#define LG 7
#define LD 4
#define UPOST 0
#define PARTX (MAPM ? 64 : 8)
__device__ __forceinline__ void mma_n224(float (&d)[112], uint32_t da, uint32_t db, int sd) {
  asm volatile("{\n.reg .pred p;\n.reg .b64 a, b;\nsetp.ne.b32 p, %114, 0;\nmov.b64 a, {%112, 0x40000040};\nmov.b64 b, {%113, 0x80000020};\n"
    "wgmma.mma_async.sync.aligned.m64n224k16.f32.bf16.bf16 {%0,%1,%2,%3,%4,%5,%6,%7,%8,%9,%10,%11,%12,%13,%14,%15,%16,%17,%18,%19,%20,%21,%22,%23,%24,%25,%26,%27,%28,%29,%30,%31,%32,%33,%34,%35,%36,%37,%38,%39,%40,%41,%42,%43,%44,%45,%46,%47,%48,%49,%50,%51,%52,%53,%54,%55,%56,%57,%58,%59,%60,%61,%62,%63,%64,%65,%66,%67,%68,%69,%70,%71,%72,%73,%74,%75,%76,%77,%78,%79,%80,%81,%82,%83,%84,%85,%86,%87,%88,%89,%90,%91,%92,%93,%94,%95,%96,%97,%98,%99,%100,%101,%102,%103,%104,%105,%106,%107,%108,%109,%110,%111}, a, b, p, 1, 1, 0, 1;\n}\n"
    : "+f"(d[0]),"+f"(d[1]),"+f"(d[2]),"+f"(d[3]),"+f"(d[4]),"+f"(d[5]),"+f"(d[6]),"+f"(d[7]),"+f"(d[8]),"+f"(d[9]),"+f"(d[10]),"+f"(d[11]),"+f"(d[12]),"+f"(d[13]),"+f"(d[14]),"+f"(d[15]),"+f"(d[16]),"+f"(d[17]),"+f"(d[18]),"+f"(d[19]),"+f"(d[20]),"+f"(d[21]),"+f"(d[22]),"+f"(d[23]),"+f"(d[24]),"+f"(d[25]),"+f"(d[26]),"+f"(d[27]),"+f"(d[28]),"+f"(d[29]),"+f"(d[30]),"+f"(d[31]),"+f"(d[32]),"+f"(d[33]),"+f"(d[34]),"+f"(d[35]),"+f"(d[36]),"+f"(d[37]),"+f"(d[38]),"+f"(d[39]),"+f"(d[40]),"+f"(d[41]),"+f"(d[42]),"+f"(d[43]),"+f"(d[44]),"+f"(d[45]),"+f"(d[46]),"+f"(d[47]),"+f"(d[48]),"+f"(d[49]),"+f"(d[50]),"+f"(d[51]),"+f"(d[52]),"+f"(d[53]),"+f"(d[54]),"+f"(d[55]),"+f"(d[56]),"+f"(d[57]),"+f"(d[58]),"+f"(d[59]),"+f"(d[60]),"+f"(d[61]),"+f"(d[62]),"+f"(d[63]),"+f"(d[64]),"+f"(d[65]),"+f"(d[66]),"+f"(d[67]),"+f"(d[68]),"+f"(d[69]),"+f"(d[70]),"+f"(d[71]),"+f"(d[72]),"+f"(d[73]),"+f"(d[74]),"+f"(d[75]),"+f"(d[76]),"+f"(d[77]),"+f"(d[78]),"+f"(d[79]),"+f"(d[80]),"+f"(d[81]),"+f"(d[82]),"+f"(d[83]),"+f"(d[84]),"+f"(d[85]),"+f"(d[86]),"+f"(d[87]),"+f"(d[88]),"+f"(d[89]),"+f"(d[90]),"+f"(d[91]),"+f"(d[92]),"+f"(d[93]),"+f"(d[94]),"+f"(d[95]),"+f"(d[96]),"+f"(d[97]),"+f"(d[98]),"+f"(d[99]),"+f"(d[100]),"+f"(d[101]),"+f"(d[102]),"+f"(d[103]),"+f"(d[104]),"+f"(d[105]),"+f"(d[106]),"+f"(d[107]),"+f"(d[108]),"+f"(d[109]),"+f"(d[110]),"+f"(d[111])
    : "r"(da), "r"(db), "r"(sd));
}
__device__ __forceinline__ void mma_n192(float (&d)[96], uint32_t da, uint32_t db, int sd) {
  asm volatile("{\n.reg .pred p;\n.reg .b64 a, b;\nsetp.ne.b32 p, %98, 0;\nmov.b64 a, {%96, 0x40000040};\nmov.b64 b, {%97, 0x40000040};\n"
    "wgmma.mma_async.sync.aligned.m64n192k16.f32.bf16.bf16 {%0,%1,%2,%3,%4,%5,%6,%7,%8,%9,%10,%11,%12,%13,%14,%15,%16,%17,%18,%19,%20,%21,%22,%23,%24,%25,%26,%27,%28,%29,%30,%31,%32,%33,%34,%35,%36,%37,%38,%39,%40,%41,%42,%43,%44,%45,%46,%47,%48,%49,%50,%51,%52,%53,%54,%55,%56,%57,%58,%59,%60,%61,%62,%63,%64,%65,%66,%67,%68,%69,%70,%71,%72,%73,%74,%75,%76,%77,%78,%79,%80,%81,%82,%83,%84,%85,%86,%87,%88,%89,%90,%91,%92,%93,%94,%95}, a, b, p, 1, 1, 0, 1;\n}\n"
    : "+f"(d[0]),"+f"(d[1]),"+f"(d[2]),"+f"(d[3]),"+f"(d[4]),"+f"(d[5]),"+f"(d[6]),"+f"(d[7]),"+f"(d[8]),"+f"(d[9]),"+f"(d[10]),"+f"(d[11]),"+f"(d[12]),"+f"(d[13]),"+f"(d[14]),"+f"(d[15]),"+f"(d[16]),"+f"(d[17]),"+f"(d[18]),"+f"(d[19]),"+f"(d[20]),"+f"(d[21]),"+f"(d[22]),"+f"(d[23]),"+f"(d[24]),"+f"(d[25]),"+f"(d[26]),"+f"(d[27]),"+f"(d[28]),"+f"(d[29]),"+f"(d[30]),"+f"(d[31]),"+f"(d[32]),"+f"(d[33]),"+f"(d[34]),"+f"(d[35]),"+f"(d[36]),"+f"(d[37]),"+f"(d[38]),"+f"(d[39]),"+f"(d[40]),"+f"(d[41]),"+f"(d[42]),"+f"(d[43]),"+f"(d[44]),"+f"(d[45]),"+f"(d[46]),"+f"(d[47]),"+f"(d[48]),"+f"(d[49]),"+f"(d[50]),"+f"(d[51]),"+f"(d[52]),"+f"(d[53]),"+f"(d[54]),"+f"(d[55]),"+f"(d[56]),"+f"(d[57]),"+f"(d[58]),"+f"(d[59]),"+f"(d[60]),"+f"(d[61]),"+f"(d[62]),"+f"(d[63]),"+f"(d[64]),"+f"(d[65]),"+f"(d[66]),"+f"(d[67]),"+f"(d[68]),"+f"(d[69]),"+f"(d[70]),"+f"(d[71]),"+f"(d[72]),"+f"(d[73]),"+f"(d[74]),"+f"(d[75]),"+f"(d[76]),"+f"(d[77]),"+f"(d[78]),"+f"(d[79]),"+f"(d[80]),"+f"(d[81]),"+f"(d[82]),"+f"(d[83]),"+f"(d[84]),"+f"(d[85]),"+f"(d[86]),"+f"(d[87]),"+f"(d[88]),"+f"(d[89]),"+f"(d[90]),"+f"(d[91]),"+f"(d[92]),"+f"(d[93]),"+f"(d[94]),"+f"(d[95])
    : "r"(da), "r"(db), "r"(sd));
}
__device__ __forceinline__ void mma_n256(float (&d)[128], uint32_t da, uint32_t db, int sd) {
  asm volatile("{\n.reg .pred p;\n.reg .b64 a, b;\nsetp.ne.b32 p, %130, 0;\nmov.b64 a, {%128, 0x40000040};\nmov.b64 b, {%129, 0x40000040};\n"
    "wgmma.mma_async.sync.aligned.m64n256k16.f32.bf16.bf16 {%0,%1,%2,%3,%4,%5,%6,%7,%8,%9,%10,%11,%12,%13,%14,%15,%16,%17,%18,%19,%20,%21,%22,%23,%24,%25,%26,%27,%28,%29,%30,%31,%32,%33,%34,%35,%36,%37,%38,%39,%40,%41,%42,%43,%44,%45,%46,%47,%48,%49,%50,%51,%52,%53,%54,%55,%56,%57,%58,%59,%60,%61,%62,%63,%64,%65,%66,%67,%68,%69,%70,%71,%72,%73,%74,%75,%76,%77,%78,%79,%80,%81,%82,%83,%84,%85,%86,%87,%88,%89,%90,%91,%92,%93,%94,%95,%96,%97,%98,%99,%100,%101,%102,%103,%104,%105,%106,%107,%108,%109,%110,%111,%112,%113,%114,%115,%116,%117,%118,%119,%120,%121,%122,%123,%124,%125,%126,%127}, a, b, p, 1, 1, 0, 1;\n}\n"
    : "+f"(d[0]),"+f"(d[1]),"+f"(d[2]),"+f"(d[3]),"+f"(d[4]),"+f"(d[5]),"+f"(d[6]),"+f"(d[7]),"+f"(d[8]),"+f"(d[9]),"+f"(d[10]),"+f"(d[11]),"+f"(d[12]),"+f"(d[13]),"+f"(d[14]),"+f"(d[15]),"+f"(d[16]),"+f"(d[17]),"+f"(d[18]),"+f"(d[19]),"+f"(d[20]),"+f"(d[21]),"+f"(d[22]),"+f"(d[23]),"+f"(d[24]),"+f"(d[25]),"+f"(d[26]),"+f"(d[27]),"+f"(d[28]),"+f"(d[29]),"+f"(d[30]),"+f"(d[31]),"+f"(d[32]),"+f"(d[33]),"+f"(d[34]),"+f"(d[35]),"+f"(d[36]),"+f"(d[37]),"+f"(d[38]),"+f"(d[39]),"+f"(d[40]),"+f"(d[41]),"+f"(d[42]),"+f"(d[43]),"+f"(d[44]),"+f"(d[45]),"+f"(d[46]),"+f"(d[47]),"+f"(d[48]),"+f"(d[49]),"+f"(d[50]),"+f"(d[51]),"+f"(d[52]),"+f"(d[53]),"+f"(d[54]),"+f"(d[55]),"+f"(d[56]),"+f"(d[57]),"+f"(d[58]),"+f"(d[59]),"+f"(d[60]),"+f"(d[61]),"+f"(d[62]),"+f"(d[63]),"+f"(d[64]),"+f"(d[65]),"+f"(d[66]),"+f"(d[67]),"+f"(d[68]),"+f"(d[69]),"+f"(d[70]),"+f"(d[71]),"+f"(d[72]),"+f"(d[73]),"+f"(d[74]),"+f"(d[75]),"+f"(d[76]),"+f"(d[77]),"+f"(d[78]),"+f"(d[79]),"+f"(d[80]),"+f"(d[81]),"+f"(d[82]),"+f"(d[83]),"+f"(d[84]),"+f"(d[85]),"+f"(d[86]),"+f"(d[87]),"+f"(d[88]),"+f"(d[89]),"+f"(d[90]),"+f"(d[91]),"+f"(d[92]),"+f"(d[93]),"+f"(d[94]),"+f"(d[95]),"+f"(d[96]),"+f"(d[97]),"+f"(d[98]),"+f"(d[99]),"+f"(d[100]),"+f"(d[101]),"+f"(d[102]),"+f"(d[103]),"+f"(d[104]),"+f"(d[105]),"+f"(d[106]),"+f"(d[107]),"+f"(d[108]),"+f"(d[109]),"+f"(d[110]),"+f"(d[111]),"+f"(d[112]),"+f"(d[113]),"+f"(d[114]),"+f"(d[115]),"+f"(d[116]),"+f"(d[117]),"+f"(d[118]),"+f"(d[119]),"+f"(d[120]),"+f"(d[121]),"+f"(d[122]),"+f"(d[123]),"+f"(d[124]),"+f"(d[125]),"+f"(d[126]),"+f"(d[127])
    : "r"(da), "r"(db), "r"(sd));
}
__device__ __forceinline__ void mma_n128(float (&d)[128], uint32_t da, uint32_t db, int sd) {
  asm volatile("{\n.reg .pred p;\n.reg .b64 a, b;\nsetp.ne.b32 p, %66, 0;\nmov.b64 a, {%64, 0x40000040};\nmov.b64 b, {%65, 0x40000040};\n"
    "wgmma.mma_async.sync.aligned.m64n128k16.f32.bf16.bf16 {%0,%1,%2,%3,%4,%5,%6,%7,%8,%9,%10,%11,%12,%13,%14,%15,%16,%17,%18,%19,%20,%21,%22,%23,%24,%25,%26,%27,%28,%29,%30,%31,%32,%33,%34,%35,%36,%37,%38,%39,%40,%41,%42,%43,%44,%45,%46,%47,%48,%49,%50,%51,%52,%53,%54,%55,%56,%57,%58,%59,%60,%61,%62,%63}, a, b, p, 1, 1, 0, 1;\n}\n"
    : "+f"(d[0]),"+f"(d[1]),"+f"(d[2]),"+f"(d[3]),"+f"(d[4]),"+f"(d[5]),"+f"(d[6]),"+f"(d[7]),"+f"(d[8]),"+f"(d[9]),"+f"(d[10]),"+f"(d[11]),"+f"(d[12]),"+f"(d[13]),"+f"(d[14]),"+f"(d[15]),"+f"(d[16]),"+f"(d[17]),"+f"(d[18]),"+f"(d[19]),"+f"(d[20]),"+f"(d[21]),"+f"(d[22]),"+f"(d[23]),"+f"(d[24]),"+f"(d[25]),"+f"(d[26]),"+f"(d[27]),"+f"(d[28]),"+f"(d[29]),"+f"(d[30]),"+f"(d[31]),"+f"(d[32]),"+f"(d[33]),"+f"(d[34]),"+f"(d[35]),"+f"(d[36]),"+f"(d[37]),"+f"(d[38]),"+f"(d[39]),"+f"(d[40]),"+f"(d[41]),"+f"(d[42]),"+f"(d[43]),"+f"(d[44]),"+f"(d[45]),"+f"(d[46]),"+f"(d[47]),"+f"(d[48]),"+f"(d[49]),"+f"(d[50]),"+f"(d[51]),"+f"(d[52]),"+f"(d[53]),"+f"(d[54]),"+f"(d[55]),"+f"(d[56]),"+f"(d[57]),"+f"(d[58]),"+f"(d[59]),"+f"(d[60]),"+f"(d[61]),"+f"(d[62]),"+f"(d[63])
    : "r"(da), "r"(db), "r"(sd));
}
__device__ __forceinline__ void cmma(float (&d)[16], uint32_t a0, uint32_t a1, uint32_t a2, uint32_t a3, uint32_t db, int sd) {
  asm volatile("{\n.reg .pred p;\n.reg .b64 b;\nsetp.ne.b32 p, %21, 0;\nmov.b64 b, {%20, 8};\n"
    "wgmma.mma_async.sync.aligned.m64n32k16.f32.bf16.bf16 {%0,%1,%2,%3,%4,%5,%6,%7,%8,%9,%10,%11,%12,%13,%14,%15}, {%16,%17,%18,%19}, b, p, 1, 1, 0;\n}\n"
    : "+f"(d[0]),"+f"(d[1]),"+f"(d[2]),"+f"(d[3]),"+f"(d[4]),"+f"(d[5]),"+f"(d[6]),"+f"(d[7]),"+f"(d[8]),"+f"(d[9]),"+f"(d[10]),"+f"(d[11]),"+f"(d[12]),"+f"(d[13]),"+f"(d[14]),"+f"(d[15])
    : "r"(a0), "r"(a1), "r"(a2), "r"(a3), "r"(db), "r"(sd));
}
__device__ __forceinline__ void cmma128(float (&d)[64], uint32_t a0, uint32_t a1, uint32_t a2, uint32_t a3, uint32_t db, int sd) {
  asm volatile("{\n.reg .pred p;\n.reg .b64 b;\nsetp.ne.b32 p, %69, 0;\nmov.b64 b, {%68, 8};\n"
    "wgmma.mma_async.sync.aligned.m64n128k16.f32.bf16.bf16 {%0,%1,%2,%3,%4,%5,%6,%7,%8,%9,%10,%11,%12,%13,%14,%15,%16,%17,%18,%19,%20,%21,%22,%23,%24,%25,%26,%27,%28,%29,%30,%31,%32,%33,%34,%35,%36,%37,%38,%39,%40,%41,%42,%43,%44,%45,%46,%47,%48,%49,%50,%51,%52,%53,%54,%55,%56,%57,%58,%59,%60,%61,%62,%63}, {%64,%65,%66,%67}, b, p, 1, 1, 0;\n}\n"
    : "+f"(d[0]),"+f"(d[1]),"+f"(d[2]),"+f"(d[3]),"+f"(d[4]),"+f"(d[5]),"+f"(d[6]),"+f"(d[7]),"+f"(d[8]),"+f"(d[9]),"+f"(d[10]),"+f"(d[11]),"+f"(d[12]),"+f"(d[13]),"+f"(d[14]),"+f"(d[15]),"+f"(d[16]),"+f"(d[17]),"+f"(d[18]),"+f"(d[19]),"+f"(d[20]),"+f"(d[21]),"+f"(d[22]),"+f"(d[23]),"+f"(d[24]),"+f"(d[25]),"+f"(d[26]),"+f"(d[27]),"+f"(d[28]),"+f"(d[29]),"+f"(d[30]),"+f"(d[31]),"+f"(d[32]),"+f"(d[33]),"+f"(d[34]),"+f"(d[35]),"+f"(d[36]),"+f"(d[37]),"+f"(d[38]),"+f"(d[39]),"+f"(d[40]),"+f"(d[41]),"+f"(d[42]),"+f"(d[43]),"+f"(d[44]),"+f"(d[45]),"+f"(d[46]),"+f"(d[47]),"+f"(d[48]),"+f"(d[49]),"+f"(d[50]),"+f"(d[51]),"+f"(d[52]),"+f"(d[53]),"+f"(d[54]),"+f"(d[55]),"+f"(d[56]),"+f"(d[57]),"+f"(d[58]),"+f"(d[59]),"+f"(d[60]),"+f"(d[61]),"+f"(d[62]),"+f"(d[63])
    : "r"(a0), "r"(a1), "r"(a2), "r"(a3), "r"(db), "r"(sd));
}
__device__ __forceinline__ void cmma96(float (&d)[64], uint32_t a0, uint32_t a1, uint32_t a2, uint32_t a3, uint32_t db, int sd) {
  asm volatile("{\n.reg .pred p;\n.reg .b64 b;\nsetp.ne.b32 p, %53, 0;\nmov.b64 b, {%52, 8};\n"
    "wgmma.mma_async.sync.aligned.m64n96k16.f32.bf16.bf16 {%0,%1,%2,%3,%4,%5,%6,%7,%8,%9,%10,%11,%12,%13,%14,%15,%16,%17,%18,%19,%20,%21,%22,%23,%24,%25,%26,%27,%28,%29,%30,%31,%32,%33,%34,%35,%36,%37,%38,%39,%40,%41,%42,%43,%44,%45,%46,%47}, {%48,%49,%50,%51}, b, p, 1, 1, 0;\n}\n"
    : "+f"(d[0]),"+f"(d[1]),"+f"(d[2]),"+f"(d[3]),"+f"(d[4]),"+f"(d[5]),"+f"(d[6]),"+f"(d[7]),"+f"(d[8]),"+f"(d[9]),"+f"(d[10]),"+f"(d[11]),"+f"(d[12]),"+f"(d[13]),"+f"(d[14]),"+f"(d[15]),"+f"(d[16]),"+f"(d[17]),"+f"(d[18]),"+f"(d[19]),"+f"(d[20]),"+f"(d[21]),"+f"(d[22]),"+f"(d[23]),"+f"(d[24]),"+f"(d[25]),"+f"(d[26]),"+f"(d[27]),"+f"(d[28]),"+f"(d[29]),"+f"(d[30]),"+f"(d[31]),"+f"(d[32]),"+f"(d[33]),"+f"(d[34]),"+f"(d[35]),"+f"(d[36]),"+f"(d[37]),"+f"(d[38]),"+f"(d[39]),"+f"(d[40]),"+f"(d[41]),"+f"(d[42]),"+f"(d[43]),"+f"(d[44]),"+f"(d[45]),"+f"(d[46]),"+f"(d[47])
    : "r"(a0), "r"(a1), "r"(a2), "r"(a3), "r"(db), "r"(sd));
}
__device__ __forceinline__ void cmma64(float (&d)[64], uint32_t a0, uint32_t a1, uint32_t a2, uint32_t a3, uint32_t db, int sd) {
  asm volatile("{\n.reg .pred p;\n.reg .b64 b;\nsetp.ne.b32 p, %37, 0;\nmov.b64 b, {%36, 8};\n"
    "wgmma.mma_async.sync.aligned.m64n64k16.f32.bf16.bf16 {%0,%1,%2,%3,%4,%5,%6,%7,%8,%9,%10,%11,%12,%13,%14,%15,%16,%17,%18,%19,%20,%21,%22,%23,%24,%25,%26,%27,%28,%29,%30,%31}, {%32,%33,%34,%35}, b, p, 1, 1, 0;\n}\n"
    : "+f"(d[0]),"+f"(d[1]),"+f"(d[2]),"+f"(d[3]),"+f"(d[4]),"+f"(d[5]),"+f"(d[6]),"+f"(d[7]),"+f"(d[8]),"+f"(d[9]),"+f"(d[10]),"+f"(d[11]),"+f"(d[12]),"+f"(d[13]),"+f"(d[14]),"+f"(d[15]),"+f"(d[16]),"+f"(d[17]),"+f"(d[18]),"+f"(d[19]),"+f"(d[20]),"+f"(d[21]),"+f"(d[22]),"+f"(d[23]),"+f"(d[24]),"+f"(d[25]),"+f"(d[26]),"+f"(d[27]),"+f"(d[28]),"+f"(d[29]),"+f"(d[30]),"+f"(d[31])
    : "r"(a0), "r"(a1), "r"(a2), "r"(a3), "r"(db), "r"(sd));
}
__device__ __forceinline__ void cmma32(float (&d)[64], uint32_t a0, uint32_t a1, uint32_t a2, uint32_t a3, uint32_t db, int sd) {
  asm volatile("{\n.reg .pred p;\n.reg .b64 b;\nsetp.ne.b32 p, %21, 0;\nmov.b64 b, {%20, 8};\n"
    "wgmma.mma_async.sync.aligned.m64n32k16.f32.bf16.bf16 {%0,%1,%2,%3,%4,%5,%6,%7,%8,%9,%10,%11,%12,%13,%14,%15}, {%16,%17,%18,%19}, b, p, 1, 1, 0;\n}\n"
    : "+f"(d[0]),"+f"(d[1]),"+f"(d[2]),"+f"(d[3]),"+f"(d[4]),"+f"(d[5]),"+f"(d[6]),"+f"(d[7]),"+f"(d[8]),"+f"(d[9]),"+f"(d[10]),"+f"(d[11]),"+f"(d[12]),"+f"(d[13]),"+f"(d[14]),"+f"(d[15])
    : "r"(a0), "r"(a1), "r"(a2), "r"(a3), "r"(db), "r"(sd));
}
__device__ __forceinline__ void fmma(float (&d)[128], uint32_t a0, uint32_t a1, uint32_t a2, uint32_t a3, uint32_t db, int sd) {
  asm volatile("{\n.reg .pred p;\n.reg .b64 b;\nsetp.ne.b32 p, %133, 0;\nmov.b64 b, {%132, " EPSB "};\n"
    "wgmma.mma_async.sync.aligned.m64n256k16.f32.bf16.bf16 {%0,%1,%2,%3,%4,%5,%6,%7,%8,%9,%10,%11,%12,%13,%14,%15,%16,%17,%18,%19,%20,%21,%22,%23,%24,%25,%26,%27,%28,%29,%30,%31,%32,%33,%34,%35,%36,%37,%38,%39,%40,%41,%42,%43,%44,%45,%46,%47,%48,%49,%50,%51,%52,%53,%54,%55,%56,%57,%58,%59,%60,%61,%62,%63,%64,%65,%66,%67,%68,%69,%70,%71,%72,%73,%74,%75,%76,%77,%78,%79,%80,%81,%82,%83,%84,%85,%86,%87,%88,%89,%90,%91,%92,%93,%94,%95,%96,%97,%98,%99,%100,%101,%102,%103,%104,%105,%106,%107,%108,%109,%110,%111,%112,%113,%114,%115,%116,%117,%118,%119,%120,%121,%122,%123,%124,%125,%126,%127}, {%128,%129,%130,%131}, b, p, 1, 1, 1;\n}\n"
    : "+f"(d[0]),"+f"(d[1]),"+f"(d[2]),"+f"(d[3]),"+f"(d[4]),"+f"(d[5]),"+f"(d[6]),"+f"(d[7]),"+f"(d[8]),"+f"(d[9]),"+f"(d[10]),"+f"(d[11]),"+f"(d[12]),"+f"(d[13]),"+f"(d[14]),"+f"(d[15]),"+f"(d[16]),"+f"(d[17]),"+f"(d[18]),"+f"(d[19]),"+f"(d[20]),"+f"(d[21]),"+f"(d[22]),"+f"(d[23]),"+f"(d[24]),"+f"(d[25]),"+f"(d[26]),"+f"(d[27]),"+f"(d[28]),"+f"(d[29]),"+f"(d[30]),"+f"(d[31]),"+f"(d[32]),"+f"(d[33]),"+f"(d[34]),"+f"(d[35]),"+f"(d[36]),"+f"(d[37]),"+f"(d[38]),"+f"(d[39]),"+f"(d[40]),"+f"(d[41]),"+f"(d[42]),"+f"(d[43]),"+f"(d[44]),"+f"(d[45]),"+f"(d[46]),"+f"(d[47]),"+f"(d[48]),"+f"(d[49]),"+f"(d[50]),"+f"(d[51]),"+f"(d[52]),"+f"(d[53]),"+f"(d[54]),"+f"(d[55]),"+f"(d[56]),"+f"(d[57]),"+f"(d[58]),"+f"(d[59]),"+f"(d[60]),"+f"(d[61]),"+f"(d[62]),"+f"(d[63]),"+f"(d[64]),"+f"(d[65]),"+f"(d[66]),"+f"(d[67]),"+f"(d[68]),"+f"(d[69]),"+f"(d[70]),"+f"(d[71]),"+f"(d[72]),"+f"(d[73]),"+f"(d[74]),"+f"(d[75]),"+f"(d[76]),"+f"(d[77]),"+f"(d[78]),"+f"(d[79]),"+f"(d[80]),"+f"(d[81]),"+f"(d[82]),"+f"(d[83]),"+f"(d[84]),"+f"(d[85]),"+f"(d[86]),"+f"(d[87]),"+f"(d[88]),"+f"(d[89]),"+f"(d[90]),"+f"(d[91]),"+f"(d[92]),"+f"(d[93]),"+f"(d[94]),"+f"(d[95]),"+f"(d[96]),"+f"(d[97]),"+f"(d[98]),"+f"(d[99]),"+f"(d[100]),"+f"(d[101]),"+f"(d[102]),"+f"(d[103]),"+f"(d[104]),"+f"(d[105]),"+f"(d[106]),"+f"(d[107]),"+f"(d[108]),"+f"(d[109]),"+f"(d[110]),"+f"(d[111]),"+f"(d[112]),"+f"(d[113]),"+f"(d[114]),"+f"(d[115]),"+f"(d[116]),"+f"(d[117]),"+f"(d[118]),"+f"(d[119]),"+f"(d[120]),"+f"(d[121]),"+f"(d[122]),"+f"(d[123]),"+f"(d[124]),"+f"(d[125]),"+f"(d[126]),"+f"(d[127])
    : "r"(a0), "r"(a1), "r"(a2), "r"(a3), "r"(db), "r"(sd));
}
__device__ __forceinline__ void fmma(float (&d)[96], uint32_t a0, uint32_t a1, uint32_t a2, uint32_t a3, uint32_t db, int sd) {
  asm volatile("{\n.reg .pred p;\n.reg .b64 b;\nsetp.ne.b32 p, %101, 0;\nmov.b64 b, {%100, " EPSB "};\n"
    "wgmma.mma_async.sync.aligned.m64n192k16.f32.bf16.bf16 {%0,%1,%2,%3,%4,%5,%6,%7,%8,%9,%10,%11,%12,%13,%14,%15,%16,%17,%18,%19,%20,%21,%22,%23,%24,%25,%26,%27,%28,%29,%30,%31,%32,%33,%34,%35,%36,%37,%38,%39,%40,%41,%42,%43,%44,%45,%46,%47,%48,%49,%50,%51,%52,%53,%54,%55,%56,%57,%58,%59,%60,%61,%62,%63,%64,%65,%66,%67,%68,%69,%70,%71,%72,%73,%74,%75,%76,%77,%78,%79,%80,%81,%82,%83,%84,%85,%86,%87,%88,%89,%90,%91,%92,%93,%94,%95}, {%96,%97,%98,%99}, b, p, 1, 1, 1;\n}\n"
    : "+f"(d[0]),"+f"(d[1]),"+f"(d[2]),"+f"(d[3]),"+f"(d[4]),"+f"(d[5]),"+f"(d[6]),"+f"(d[7]),"+f"(d[8]),"+f"(d[9]),"+f"(d[10]),"+f"(d[11]),"+f"(d[12]),"+f"(d[13]),"+f"(d[14]),"+f"(d[15]),"+f"(d[16]),"+f"(d[17]),"+f"(d[18]),"+f"(d[19]),"+f"(d[20]),"+f"(d[21]),"+f"(d[22]),"+f"(d[23]),"+f"(d[24]),"+f"(d[25]),"+f"(d[26]),"+f"(d[27]),"+f"(d[28]),"+f"(d[29]),"+f"(d[30]),"+f"(d[31]),"+f"(d[32]),"+f"(d[33]),"+f"(d[34]),"+f"(d[35]),"+f"(d[36]),"+f"(d[37]),"+f"(d[38]),"+f"(d[39]),"+f"(d[40]),"+f"(d[41]),"+f"(d[42]),"+f"(d[43]),"+f"(d[44]),"+f"(d[45]),"+f"(d[46]),"+f"(d[47]),"+f"(d[48]),"+f"(d[49]),"+f"(d[50]),"+f"(d[51]),"+f"(d[52]),"+f"(d[53]),"+f"(d[54]),"+f"(d[55]),"+f"(d[56]),"+f"(d[57]),"+f"(d[58]),"+f"(d[59]),"+f"(d[60]),"+f"(d[61]),"+f"(d[62]),"+f"(d[63]),"+f"(d[64]),"+f"(d[65]),"+f"(d[66]),"+f"(d[67]),"+f"(d[68]),"+f"(d[69]),"+f"(d[70]),"+f"(d[71]),"+f"(d[72]),"+f"(d[73]),"+f"(d[74]),"+f"(d[75]),"+f"(d[76]),"+f"(d[77]),"+f"(d[78]),"+f"(d[79]),"+f"(d[80]),"+f"(d[81]),"+f"(d[82]),"+f"(d[83]),"+f"(d[84]),"+f"(d[85]),"+f"(d[86]),"+f"(d[87]),"+f"(d[88]),"+f"(d[89]),"+f"(d[90]),"+f"(d[91]),"+f"(d[92]),"+f"(d[93]),"+f"(d[94]),"+f"(d[95])
    : "r"(a0), "r"(a1), "r"(a2), "r"(a3), "r"(db), "r"(sd));
}

__device__ __forceinline__ void wg_fence() { asm volatile("wgmma.fence.sync.aligned;" ::: "memory"); }
__device__ __forceinline__ void wg_commit() { asm volatile("wgmma.commit_group.sync.aligned;" ::: "memory"); }
template <int N> __device__ __forceinline__ void wg_wait() { asm volatile("wgmma.wait_group.sync.aligned %0;" ::"n"(N) : "memory"); }
__device__ __forceinline__ uint32_t mkdesc(uint32_t addr, uint32_t lbo) { return ((addr & 0x3FFFF) >> 4) | ((lbo >> 4) << 16); }
__device__ __forceinline__ uint32_t smem_u32(const void* p) { return (uint32_t)__cvta_generic_to_shared(p); }
__device__ __forceinline__ void mbar_init(uint32_t bar, uint32_t cnt) { asm volatile("mbarrier.init.shared::cta.b64 [%0], %1;" ::"r"(bar), "r"(cnt) : "memory"); }
__device__ __forceinline__ void mbar_expect_tx(uint32_t bar, uint32_t bytes) { asm volatile("mbarrier.arrive.expect_tx.shared::cta.b64 _, [%0], %1;" ::"r"(bar), "r"(bytes) : "memory"); }
__device__ __forceinline__ void mbar_arrive(uint32_t bar) { asm volatile("mbarrier.arrive.shared::cta.b64 _, [%0];" ::"r"(bar) : "memory"); }
__device__ __forceinline__ uint32_t mapa(uint32_t a, uint32_t cta) { uint32_t r; asm volatile("mapa.shared::cluster.u32 %0, %1, %2;" : "=r"(r) : "r"(a), "r"(cta)); return r; }
__device__ __forceinline__ void mbar_arrive_remote(uint32_t rbar) { asm volatile("mbarrier.arrive.shared::cluster.b64 _, [%0];" ::"r"(rbar) : "memory"); }
__device__ __forceinline__ void mbar_arrive_remote4(uint32_t rbar) { asm volatile("mbarrier.arrive.shared::cluster.b64 _, [%0], 4;" ::"r"(rbar) : "memory"); }
__device__ __forceinline__ void mbar_wait(uint32_t bar, uint32_t parity) {
  asm volatile("{\n.reg .pred p;\n.reg .u32 n;\nmov.u32 n, 0;\nLW:\nmbarrier.try_wait.parity.shared::cta.b64 p, [%0], %1;\n@p bra LD;\n"
               "add.u32 n, n, 1;\nsetp.lt.u32 p, n, 4000000;\n@p bra LW;\ntrap;\nLD:\n}\n" ::"r"(bar), "r"(parity) : "memory");
}
__device__ __forceinline__ void mbar_waitf(uint32_t bar, uint32_t parity) {
  asm volatile("{\n.reg .pred p;\n.reg .u32 n;\nmbarrier.try_wait.parity.shared::cta.b64 p, [%0], %1;\n@p bra LD;\nmov.u32 n, 0;\nLW:\nmbarrier.try_wait.parity.shared::cta.b64 p, [%0], %1;\n@p bra LD;\n"
               "add.u32 n, n, 1;\nsetp.lt.u32 p, n, 4000000;\n@p bra LW;\ntrap;\nLD:\n}\n" ::"r"(bar), "r"(parity) : "memory");
}
__device__ __forceinline__ void tma2d(uint32_t dst, const CUtensorMap* m, uint32_t bar, int c0, int c1) {
  asm volatile("cp.async.bulk.tensor.2d.shared::cluster.global.mbarrier::complete_tx::bytes [%0], [%1, {%3, %4}], [%2];" ::"r"(dst), "l"(m), "r"(bar), "r"(c0), "r"(c1) : "memory");
}
__device__ __forceinline__ void tma3d_mc(uint32_t dst, const CUtensorMap* m, uint32_t bar, int c0, int c1, int c2, uint16_t mask) {
  asm volatile("cp.async.bulk.tensor.3d.shared::cluster.global.mbarrier::complete_tx::bytes.multicast::cluster [%0], [%1, {%3, %4, %5}], [%2], %6;" ::"r"(dst), "l"(m), "r"(bar), "r"(c0), "r"(c1), "r"(c2), "h"(mask) : "memory");
}
__device__ __forceinline__ void tma5d_mc(uint32_t dst, const CUtensorMap* m, uint32_t bar, int c0, int c4) {
  asm volatile("cp.async.bulk.tensor.5d.shared::cluster.global.mbarrier::complete_tx::bytes.multicast::cluster [%0], [%1, {%3, %5, %5, %5, %4}], [%2], %6;" ::"r"(dst), "l"(m), "r"(bar), "r"(c0), "r"(c4), "r"(0), "h"((uint16_t)3) : "memory");
}
__device__ __forceinline__ void tma2d_store(const CUtensorMap* m, uint32_t src, int c0, int c1) {
  asm volatile("cp.async.bulk.tensor.2d.global.shared::cta.bulk_group [%0, {%2, %3}], [%1];" ::"l"(m), "r"(src), "r"(c0), "r"(c1) : "memory");
}
__device__ __forceinline__ void bulk_g2s(uint32_t dst, const void* src, uint32_t bytes, uint32_t bar) {
  asm volatile("cp.async.bulk.shared::cluster.global.mbarrier::complete_tx::bytes [%0], [%1], %2, [%3];" ::"r"(dst), "l"(src), "r"(bytes), "r"(bar) : "memory");
}
__device__ __forceinline__ void fence_async() { asm volatile("fence.proxy.async.global;" ::: "memory"); }
__device__ __forceinline__ void bar_sync(int id, int n) { asm volatile("bar.sync %0, %1;" ::"r"(id), "r"(n) : "memory"); }
__device__ __forceinline__ void bar_arrive(int id, int n) { asm volatile("bar.arrive %0, %1;" ::"r"(id), "r"(n) : "memory"); }
__device__ __forceinline__ uint32_t lds32(uint32_t a) { uint32_t v; asm volatile("ld.volatile.shared.b32 %0, [%1];" : "=r"(v) : "r"(a)); return v; }
__device__ __forceinline__ uint32_t lds32p(uint32_t a, bool on) { uint32_t v; asm volatile("{\n.reg .pred p;\nsetp.ne.s32 p, %2, 0;\nmov.u32 %0, 0;\n@p ld.volatile.shared.b32 %0, [%1];\n}\n" : "=r"(v) : "r"(a), "r"((int)on)); return v; }
__device__ __forceinline__ void sts128(uint32_t a, float x, float y, float z, float w) { asm volatile("st.shared.v4.f32 [%0], {%1,%2,%3,%4};" ::"r"(a), "f"(x), "f"(y), "f"(z), "f"(w) : "memory"); }
__device__ __forceinline__ void sts64(uint32_t a, uint32_t x, uint32_t y) { asm volatile("st.shared.v2.b32 [%0], {%1,%2};" ::"r"(a), "r"(x), "r"(y) : "memory"); }
template <int OFF> __device__ __forceinline__ uint2 lds64p(uint32_t a, bool on) {
  uint2 v;
  asm volatile("{\n.reg .pred p;\nsetp.ne.s32 p, %3, 0;\nmov.u32 %0, 0;\nmov.u32 %1, 0;\n@p ld.shared.v2.b32 {%0,%1}, [%2+%4];\n}\n" : "=r"(v.x), "=r"(v.y) : "r"(a), "r"((int)on), "n"(OFF) : "memory");
  return v;
}
__device__ __forceinline__ uint2 lds64(uint32_t a) { uint2 v; asm volatile("ld.shared.v2.b32 {%0,%1}, [%2];" : "=r"(v.x), "=r"(v.y) : "r"(a) : "memory"); return v; }
__device__ __forceinline__ float4 lds128(uint32_t a) { float4 v; asm volatile("ld.shared.v4.f32 {%0,%1,%2,%3}, [%4];" : "=f"(v.x), "=f"(v.y), "=f"(v.z), "=f"(v.w) : "r"(a) : "memory"); return v; }
__device__ __forceinline__ void stg128(void* p, uint32_t a, uint32_t b, uint32_t c, uint32_t d) { asm volatile("st.global.v4.b32 [%0], {%1,%2,%3,%4};" ::"l"(p), "r"(a), "r"(b), "r"(c), "r"(d) : "memory"); }
__device__ __forceinline__ void sts128u(uint32_t a, uint32_t x, uint32_t y, uint32_t z, uint32_t w) { asm volatile("st.shared.v4.b32 [%0], {%1,%2,%3,%4};" ::"r"(a), "r"(x), "r"(y), "r"(z), "r"(w) : "memory"); }
__device__ __forceinline__ void signal(int c, unsigned inc) { asm volatile("red.release.gpu.global.add.u32 [%0], %1;" ::"l"(g_cnt + c * 32), "r"(inc) : "memory"); }
__device__ __forceinline__ unsigned ld_epoch() { unsigned v; asm volatile("ld.relaxed.gpu.global.u32 %0, [%1];" : "=r"(v) : "l"(g_cnt + C_TK * 32) : "memory"); return (v >> 7) + 1; }
constexpr int SPINMAX = 1000000;
__device__ __forceinline__ void spin_guard(int n) { asm volatile("{\n.reg .pred p;\nsetp.gt.s32 p, %0, 1000000;\n@p trap;\n}\n" ::"r"(n)); }
__device__ __forceinline__ void wait_cnt(int c, unsigned ep) {
  unsigned v, n = 0;
  while (true) {
    asm volatile("ld.acquire.gpu.global.u32 %0, [%1];" : "=r"(v) : "l"(g_cnt + c * 32) : "memory");
    if ((int)(v - (ep << 7)) >= 0) break;
    spin_guard(++n);
    __nanosleep(20);
  }
}
__device__ __forceinline__ uint4 ldg128_rlx(const void* p) { uint4 v; asm volatile("ld.relaxed.gpu.global.v4.b32 {%0,%1,%2,%3}, [%4];" : "=r"(v.x), "=r"(v.y), "=r"(v.z), "=r"(v.w) : "l"(p) : "memory"); return v; }
__device__ __forceinline__ uint2 ldg64_rlx(const void* p) { uint2 v; asm volatile("ld.relaxed.gpu.global.v2.b32 {%0,%1}, [%2];" : "=r"(v.x), "=r"(v.y) : "l"(p) : "memory"); return v; }
__device__ __forceinline__ void stg64_rlx(void* p, uint32_t a, uint32_t b) { asm volatile("st.relaxed.gpu.global.v2.b32 [%0], {%1,%2};" ::"l"(p), "r"(a), "r"(b) : "memory"); }
__device__ __forceinline__ void stg128_rlx(void* p, uint32_t a, uint32_t b, uint32_t c, uint32_t d) { asm volatile("st.relaxed.gpu.global.v4.b32 [%0], {%1,%2,%3,%4};" ::"l"(p), "r"(a), "r"(b), "r"(c), "r"(d) : "memory"); }
__device__ __forceinline__ uint32_t pack2(float lo, float hi) { uint32_t r; asm("cvt.rn.bf16x2.f32 %0, %1, %2;" : "=r"(r) : "f"(hi), "f"(lo)); return r; }
__device__ __forceinline__ float blo(uint32_t v) { return __uint_as_float(v << 16); }
__device__ __forceinline__ float bhi(uint32_t v) { return __uint_as_float(v & 0xffff0000u); }
__device__ __forceinline__ float rbf(float x) { return __bfloat162float(__float2bfloat16_rn(x)); }
__device__ __forceinline__ uint32_t hmul2(uint32_t a, uint32_t b) { uint32_t r; asm("mul.rn.bf16x2 %0, %1, %2;" : "=r"(r) : "r"(a), "r"(b)); return r; }
__device__ __forceinline__ uint32_t hadd2(uint32_t a, uint32_t b) { uint32_t r; asm("add.rn.bf16x2 %0, %1, %2;" : "=r"(r) : "r"(a), "r"(b)); return r; }
__device__ __forceinline__ uint32_t hfma2(uint32_t a, uint32_t b, uint32_t c) { uint32_t r; asm("fma.rn.bf16x2 %0, %1, %2, %3;" : "=r"(r) : "r"(a), "r"(b), "r"(c)); return r; }
__device__ __forceinline__ uint32_t ldg32(const void* p) { uint32_t v; asm volatile("ld.global.nc.b32 %0, [%1];" : "=r"(v) : "l"(p)); return v; }
__device__ __forceinline__ uint4 ldg128(const void* p) { uint4 v; asm volatile("ld.global.nc.v4.b32 {%0,%1,%2,%3}, [%4];" : "=r"(v.x), "=r"(v.y), "=r"(v.z), "=r"(v.w) : "l"(p)); return v; }
__device__ __forceinline__ uint2 ldg64(const void* p) { uint2 v; asm volatile("ld.global.nc.v2.b32 {%0,%1}, [%2];" : "=r"(v.x), "=r"(v.y) : "l"(p)); return v; }
__device__ __forceinline__ uint32_t ldg16(const void* p, int on) { uint32_t v; asm volatile("{\n.reg .pred p;\nsetp.ne.s32 p, %2, 0;\nmov.u32 %0, 0;\n@p ld.global.nc.u16 %0, [%1];\n}\n" : "=r"(v) : "l"(p), "r"(on)); return v; }
__device__ __forceinline__ void tma3d(uint32_t dst, const CUtensorMap* m, uint32_t bar, int c0, int c1) {
  asm volatile("cp.async.bulk.tensor.3d.shared::cluster.global.mbarrier::complete_tx::bytes [%0], [%1, {%3, %4, %5}], [%2];" ::"r"(dst), "l"(m), "r"(bar), "r"(c0), "r"(c1), "r"(0) : "memory");
}
__device__ __forceinline__ void tma3d3(uint32_t dst, const CUtensorMap* m, uint32_t bar, int c0, int c1, int c2) {
  asm volatile("cp.async.bulk.tensor.3d.shared::cluster.global.mbarrier::complete_tx::bytes [%0], [%1, {%3, %4, %5}], [%2];" ::"r"(dst), "l"(m), "r"(bar), "r"(c0), "r"(c1), "r"(c2) : "memory");
}
__device__ __forceinline__ void ldsm4t(uint32_t* r, uint32_t a) { asm volatile("ldmatrix.sync.aligned.m8n8.x4.trans.shared.b16 {%0,%1,%2,%3}, [%4];" : "=r"(r[0]), "=r"(r[1]), "=r"(r[2]), "=r"(r[3]) : "r"(a) : "memory"); }
__device__ __forceinline__ uint32_t movm(uint32_t v) { uint32_t r; asm volatile("movmatrix.sync.aligned.m8n8.trans.b16 %0, %1;" : "=r"(r) : "r"(v)); return r; }
__device__ __forceinline__ float ex2(float x) { float r; asm("ex2.approx.ftz.f32 %0, %1;" : "=f"(r) : "f"(x)); return r; }
__device__ __forceinline__ float rcp(float x) { float r; asm("rcp.approx.ftz.f32 %0, %1;" : "=f"(r) : "f"(x)); return r; }
constexpr float LOG2E = 1.4426950408889634f;
__device__ __forceinline__ float mish(float h, float m1) {
  const float e = ex2(h * 1.4426950408889634f);
  return fmaf(h, rcp(fmaf(e, fmaf(e, -0.5f, m1), -1.f)), h);
}
__device__ __forceinline__ float mish2(float t, float m1) {
  const float e = ex2(t);
  return fmaf(-t, rcp(fmaf(e, fmaf(e, -0.5f, m1), -1.f)), -t);
}
__device__ __forceinline__ void silu4(float (&t)[4]) {
  float a[4];
#pragma unroll
  for (int i = 0; i < 4; i++) a[i] = 1.f + ex2(fminf(t[i], 31.f));
  const float p = a[0] * a[1], q = a[2] * a[3], r = rcp(p * q) * -0.6931471805599453f, rp = r * q, rq = r * p;
  t[0] *= a[1] * rp; t[1] *= a[0] * rp; t[2] *= a[3] * rq; t[3] *= a[2] * rq;
}

__device__ __forceinline__ uint32_t cpy(uint32_t v, uint32_t z) { uint32_t r; asm volatile("mad.lo.u32 %0, %2, %2, %1;" : "=r"(r) : "r"(v), "r"(z)); return r; }
__device__ __forceinline__ uint32_t cpx(uint32_t v, uint32_t z) { uint32_t r; asm volatile("xor.b32 %0, %1, %2;" : "=r"(r) : "r"(v), "r"(z)); return r; }
template <int HG> __device__ __forceinline__ void loadP(uint32_t (&x)[16], uint32_t hb, int p) {
  const uint32_t b = hb + (HG >> 1) * 1024 + (HG & 1) * 128;
#pragma unroll
  for (int j = 3 * p; j < 3 * p + 3; j++) if (!(SHW && (HG & 1) && j == 0)) x[j ? 2 * j - 1 : 0] = lds32(b + j * 16);
}
template <int HG> __device__ __forceinline__ void loadA(uint32_t (&x)[16], uint32_t hb) { loadP<HG>(x, hb, 0); loadP<HG>(x, hb, 1); loadP<HG>(x, hb, 2); }
__device__ __forceinline__ void dupA(uint32_t (&x)[16], uint32_t z) {
#pragma unroll
  for (int r = 0; r < 4; r++) {
    if (FDUP == 4 && r < 3) x[4 * r + 4] = cpx(x[4 * r + 3], z);
    x[4 * r + 2] = FDUP == 2 ? cpx(x[4 * r + 1], z) : cpy(x[4 * r + 1], z);
    if (FDUP != 4 && r < 3) x[4 * r + 4] = FDUP == 2 || FDUP == 3 ? cpy(x[4 * r + 3], z) : cpx(x[4 * r + 3], z);
  }
}
template <int HG> __device__ __forceinline__ void mmaG(float (&d)[64], uint32_t (&x)[16], uint32_t dbase) {
  wg_fence();
#pragma unroll
  for (int rr = 0; rr < 4; rr++) {
    constexpr int SP = HG >> 1;
    const uint32_t db = dbase + (SP * 32 + (HG & 1) * 4 + rr);
    const int sd = (HG | rr) != 0;
    if (SP == 0) cmma128(d, x[4 * rr], x[4 * rr + 1], x[4 * rr + 2], x[4 * rr + 3], db, sd);
    if (SP == 1) cmma96(d, x[4 * rr], x[4 * rr + 1], x[4 * rr + 2], x[4 * rr + 3], db, sd);
    if (SP == 2) cmma64(d, x[4 * rr], x[4 * rr + 1], x[4 * rr + 2], x[4 * rr + 3], db, sd);
    if (SP == 3) cmma32(d, x[4 * rr], x[4 * rr + 1], x[4 * rr + 2], x[4 * rr + 3], db, sd);
  }
  wg_commit();
}

struct Params {
  const bf16 *x, *k, *v, *shk, *hk, *Dv, *b1, *w1;
  uint32_t zero;
};

__device__ __forceinline__ void act_chunk(const uint32_t* h, bf16* dst, float k, float m1 = -1.f) {
  uint32_t o[4];
#pragma unroll
  for (int i = 0; i < 4; i++) o[i] = pack2(mish2(blo(h[i]) * k, m1), mish2(bhi(h[i]) * k, m1));
  stg128(dst, o[0], o[1], o[2], o[3]);
}

template <class F> __device__ __forceinline__ void ustep(bool on, uint32_t base, uint32_t lo, uint32_t bar, uint32_t par, uint32_t rel, bool dorel, uint8_t* dst, uint2 sw, uint32_t& c0_, uint32_t& c1_, int sl, F&& mid) {
  uint32_t Q[10], V[8];
  if (on) {
    mbar_waitf(bar, par);
    ldsm4t(Q + 6, base + lo + 4096); ldsm4t(Q + 2, base + lo); ldsm4t(V, base + (lo ^ 3072) + 8192); ldsm4t(V + 4, base + (lo ^ 3072) + 12288);
  }
  mid();
  if (!on) return;
  const uint32_t n0 = __shfl_sync(0xffffffff, Q[8], sl), n1 = __shfl_sync(0xffffffff, Q[9], sl);
  asm volatile("" ::"r"(Q[2]), "r"(V[0]), "r"(V[4]) : "memory");
  __syncwarp();
  if (dorel) mbar_arrive(rel);
  const uint32_t w0 = __byte_perm(sw.x, 0, 0x1010), w1 = __byte_perm(sw.x, 0, 0x3232), w2 = __byte_perm(sw.y, 0, 0x1010), w3 = __byte_perm(sw.y, 0, 0x3232);
  Q[0] = (sl & 3) == 0 ? c0_ : n0; Q[1] = (sl & 3) == 0 ? c1_ : n1;
  c0_ = n0; c1_ = n1;
  uint32_t pm = __byte_perm(Q[9], Q[8], 0x5432);
#pragma unroll
  for (int j = 7; j >= 0; j--) {
    const uint32_t pc = __byte_perm(Q[j + 1], Q[j], 0x5432);
    V[j ^ 3] = hmul2(hfma2(Q[j + 2], w0, hfma2(pm, w1, hfma2(Q[j + 1], w2, hmul2(pc, w3)))), V[j ^ 3]);
    pm = pc;
    if (j == 4) stg128(dst, V[4], V[5], V[6], V[7]);
  }
  stg128(dst + UARR, V[0], V[1], V[2], V[3]);
}

__device__ __forceinline__ int chbase() { int c; asm volatile("mov.u32 %0, %%ctaid.x;" : "=r"(c)); return c * 7 + (c >> 7) * (c & 3) * 9; }
#define LOCALS const uint32_t tid = threadIdx.x; \
  const int lane = tid & 31, w = (tid >> 5) & 3, g = lane >> 2, q = lane & 3, wg = tid >> 7; (void)w; (void)g; (void)q; (void)wg

template <int NJ> __device__ __forceinline__ uint2 g1_fix(float (&d)[4 * NJ], uint32_t s_st, uint32_t s_cb) {
  LOCALS;
  const uint2 st = lds64(s_st + (wg * 32 + w * 8 + g) * 8);
  const uint32_t sel = q & 1 ? 0x3210 : 0x3232, a0 = __byte_perm(st.x, 0, sel), a1 = __byte_perm(st.y, 0, sel), db = mkdesc(s_cb, EPS ? 64 : 0);
  uint32_t f[4] = {q < 2 ? a0 : 0, q < 2 ? a1 : 0, 0, 0};
  asm volatile("" : "+r"(f[0]), "+r"(f[1]), "+r"(f[2]), "+r"(f[3]));
  if (EPZ) wg_wait<0>();
  wg_fence();
  fmma(d, f[0], f[1], f[2], f[3], db, 1);
  wg_commit();
  return st;
}
template <int NJ> __device__ __forceinline__ void g1_epi(const float (&d)[4 * NJ], uint32_t (&h)[2 * NJ], uint2 st) {
  const float rs0 = SCL ? 1.f : rcp(blo(st.x)), rs1 = SCL ? 1.f : rcp(blo(st.y));
#pragma unroll
  for (int j = 0; j < NJ; j++) {
    h[(j >> 2) * 8 + (j & 3)] = pack2(d[4 * j] * rs0, d[4 * j + 1] * rs0);
    h[(j >> 2) * 8 + 4 + (j & 3)] = pack2(d[4 * j + 2] * rs1, d[4 * j + 3] * rs1);
  }
}
#define WCLK(x)
#define WOUT(i)
#define G1COMMON(MMA, NS, SPL, PRE) \
  const int wu = WGU; \
  uint32_t wa_ = 0, wb_ = 0; (void)wa_; (void)wb_; \
  const uint32_t da0 = mkdesc(sb, 16) + wu * 512, db0 = mkdesc(sb + 16384, 4096); \
  auto kstep = [&](uint32_t kb, auto&& pre) { \
    const uint32_t st = kb & 3, so = st * (STAGE >> 4); \
    WCLK(wa_ -=); \
    mbar_waitf(bfull + st * 8, (kb >> 2) & 1); \
    WCLK(wa_ +=); \
    if (PRE == 1) pre(); \
    wg_fence(); \
    _Pragma("unroll") for (int kk = 0; kk < 4; kk++) { \
      MMA(d, da0 + (so + kk * 2), db0 + (so + (kk & 1) * 128 + (kk >> 1) * NS * 256), kk || kb); \
      if (PRE == 2 && kk == 0) pre(); \
      if (kk == SPL) { \
        wg_commit(); \
        WCLK(wb_ -=); \
        wg_wait<1>(); \
        WCLK(wb_ +=); \
        if (kb == 7 || kb == 15) WOUT(111 + (4 - NS) * 8 + (kb >> 3) * 4); \
        if (kb && lane == 0) { mbar_arrive_remote(e0 + ((kb - 1) & 3) * 8); mbar_arrive_remote(e1 + ((kb - 1) & 3) * 8); } \
        if (kk < 3) wg_fence(); \
      } \
    } \
    if (SPL < 3) wg_commit(); \
  }; \
  const int C = ((mp & 3) * 2 + rank) * NS + min(w, NS - 1); \
  const uint32_t csb = sb + 16384 + wg * NS * 4096 + (C >> 3) * 4096 + g * 128 + (((C ^ g) & 7) << 4) + q * 4; \
  float cs0 = 0.f, cs1 = 0.f; \
  auto kstepx = [&](uint32_t kb, bool on, auto&& pre, auto&& mid) { \
    uint32_t v[4]; \
    if (!VU) v[0] = v[1] = v[2] = v[3] = 0; \
    auto ld = [&]() { \
      if (on) { _Pragma("unroll") for (int r = 0; r < 4; r++) v[r] = lds32(csb + (kb & 3) * STAGE + r * 1024); } \
      pre(); \
    }; \
    kstep(kb, ld); \
    if (PRE == 0) ld(); \
    mid(); \
    if (on) { cs0 += (blo(v[0]) + blo(v[1])) + (blo(v[2]) + blo(v[3])); cs1 += (bhi(v[0]) + bhi(v[1])) + (bhi(v[2]) + bhi(v[3])); } \
    asm volatile("" : "+f"(cs0), "+f"(cs1)); \
  }; \
  auto cs_pub = [&](uint32_t par) { \
    _Pragma("unroll") for (int o = 4; o < 32; o *= 2) { cs0 += __shfl_xor_sync(0xffffffff, cs0, o); cs1 += __shfl_xor_sync(0xffffffff, cs1, o); } \
    if (lane < 4) stg64_rlx(g_csp + ((mp >> 2) * 2 + wg) * 4096 + jn * 512 + (4 - NS) * 256 + C * 8 + lane * 2, (__float_as_uint(cs0) & ~1u) | par, __float_as_uint(cs1)); \
    bar_arrive(NB_CS, 288); \
  }

#define WGU __shfl_sync(0xffffffff, wg, 0)
enum { NB_ORD0 = 1, NB_ORD1 = 2, NB_WG0 = 3, NB_WG1 = 4, NB_CS = 5, NB_ACT = 6, NB_Y = 7, NB_U = 11, NB_ST = 12, NB_PRI = 13 };

__global__ void __cluster_dims__(2, 1, 1) __launch_bounds__(384, 1)
fused_kernel(const __grid_constant__ CUtensorMap m_x, const __grid_constant__ CUtensorMap m_w1, const __grid_constant__ CUtensorMap m_w1b, const __grid_constant__ CUtensorMap m_act,
             const __grid_constant__ CUtensorMap m_w2, const __grid_constant__ CUtensorMap m_y, const __grid_constant__ CUtensorMap m_out,
             const __grid_constant__ CUtensorMap m_k, const __grid_constant__ CUtensorMap m_v, const Params p) {
  extern __shared__ __align__(1024) uint8_t smem_raw[];
  const uint32_t sb = smem_u32(smem_raw);
  const uint32_t bfull = sb + SM_BARS, bempty = bfull + 32, bepi = bfull + 64, bxt = bfull + 72, byf = bfull + 80, bdep = bfull + 88, bkv = bfull + 136, bhl = bfull + 152, bh = bfull + 184, bkf = bfull + 216, s_par = bfull + 224, bdx = bfull + 232;
  const uint32_t s_cb = sb + SM_CB, s_st = sb + SM_ST, s_xt = sb + SM_XT;
  const int cta = blockIdx.x, cid = cta >> 1, rank = cta & 1;
  const int mp = cid & 7, jn = cid >> 3;
  const int tm = mp * 2 + rank;
  const int tn2 = jn & 3, kh = jn >> 2;
  const int c0 = tn2 * 256 + kh * 128;
  const int rot = (mp >> 2) * 8;
  const bool ex = cta >= 128;
  if (threadIdx.x == 256) {
    asm volatile("prefetch.tensormap [%0];" ::"l"(&m_x) : "memory");
    asm volatile("prefetch.tensormap [%0];" ::"l"(&m_w1) : "memory");
    for (int s = 0; s < NST; s++) { mbar_init(bfull + s * 8, 1); mbar_init(bempty + s * 8, 16); mbar_init(bh + s * 8, 2); }
    mbar_init(bepi, 2); mbar_init(bxt, 1); mbar_init(byf, 8); mbar_init(bkf, 8); mbar_init(bdx, 1);
    for (int s = 0; s < 12; s++) mbar_init(bdep + s * 8, 1);
    if (sb & 1023) asm volatile("trap;");
    asm volatile("fence.mbarrier_init.release.cluster;" ::: "memory");
    STAMP(0);
  }
  __syncwarp();
  asm volatile("barrier.cluster.arrive.relaxed.aligned;" ::: "memory");
  if (threadIdx.x == 256 && !ex) {
    mbar_expect_tx(bfull, STAGE);
    tma3d3(sb + 16384 + rank * 16384, &m_w1, bfull, 0, rot * 64 + rank * 32, jn * 7);
    tma2d(sb, &m_x, bfull, rot * 64, tm * 128);
    tma3d3(sb + 32768 - rank * 16384, &m_w1, bfull, 0, rot * 64 + 32 - rank * 32, jn * 7);
  }
  __syncwarp();
  if (__shfl_sync(0xffffffff, threadIdx.x >> 7, 0) == 2) {
    asm volatile("setmaxnreg.dec.sync.aligned.u32 %0;" ::"n"(504 - 2 * RC));
    const int warp = (threadIdx.x >> 5) & 3, lane = threadIdx.x & 31;
    asm volatile("barrier.cluster.wait.aligned;" ::: "memory");
    if (warp == 0) {
      if (lane == 0) {
        uint32_t ph = 1;
        PSTAMP(1);
        auto ldkv = [&](uint32_t buf, uint32_t bb, int c, int r) { tma3d(buf, &m_k, bb, c, r); tma3d(buf + 8192, &m_v, bb, c, r); };
#pragma unroll 1
        for (int it = ex ? 32 : 1; it < 32; it++) {
          int st = it & 3, t = it >> 4, kb = (it + rot + 12 * t) & 15;
          uint32_t a = sb + st * STAGE, b = a + 16384;
          mbar_wait(bempty + st * 8, ph);
          const bool keep = (it >> 2) == 4;
          mbar_expect_tx(bfull + st * 8, STAGE - t * 8192 - keep * 16384);
          if (!keep) tma2d(a, &m_x, bfull + st * 8, kb * 64, tm * 128);
          tma3d_mc(b + rank * (16384 - t * 4096), t ? &m_w1b : &m_w1, bfull + st * 8, 0, kb * 64 + rank * 32, jn * 7 + t * 4, 3);
          if ((it == UWAIT || it == UWAIT + UW2) && (cta & 15) != 14) {
            const int i = it != UWAIT;
            mbar_expect_tx(bkv + i * 8, 16384);
            ldkv(s_xt + i * 16384, bkv + i * 8, (cta & 15) * 64, (cta >> 4) * 16 + i * 4);
          }
          if (it == W1K || it == W1K + 1) asm volatile("cp.async.bulk.prefetch.tensor.3d.L2.global [%0, {%1, %2, %3}];" ::"l"(&m_w1b), "r"(0), "r"(tm * 64 + (it - W1K) * 32), "r"(jn * 7 + 4) : "memory");
          if (it < 4) PSTAMP(33 + it);
          if (it == XPF) asm volatile("cp.async.bulk.prefetch.L2.global [%0], 32768;" ::"l"(p.x + (size_t)(tm * 128 + jn * 16) * D_) : "memory");
          if (st == 3) ph ^= 1;
        }
        const int chb = chbase();
        if (ex) {
#pragma unroll 1
          for (int i = 0; i < 8; i++) {
            const uint32_t bb = bdep + 8 + (i >> 1) * 8;
            if (!(i & 1)) mbar_expect_tx(bb, 32768);
            ldkv(sb + STAGE + i * 16384, bb, 896, (cta & 3) * 32 + i * 4);
          }
          mbar_expect_tx(bhl, 8192);
          bulk_g2s(sb + CH0, p.hk + (size_t)chb * S_, 4096, bhl);
          bulk_g2s(sb + CHB + CH0, p.hk + (size_t)(chb + 1) * S_, 4096, bhl);
          asm volatile("cp.async.bulk.prefetch.L2.global [%0], 24576;" ::"l"(p.hk + (size_t)(chb + 2) * S_) : "memory");
        }
        mbar_wait(bdep, 0);
        if (!ex) mbar_expect_tx(bxt, 32768);
        fence_async();
#pragma unroll 1
        for (int it = 0; it < (ex ? 16 : 4); it++) {
          const int st = it & 3;
          const bool one = it == 3 && !ex;
          if (it == 8) { wait_cnt(C_U + 15, ld_epoch()); fence_async(); }
          mbar_wait(bempty + st * 8, ph);
          PSTAMP(66 + st);
          if (it || !ex) mbar_expect_tx(bhl + st * 8, 8192);
          mbar_expect_tx(bfull + st * 8, one ? UCH : 2 * UCH);
#pragma unroll 1
          for (int j = 0; j < 2; j++) {
            int ch = chb + it * 2 + j + (it & 8) * 6;
            uint32_t dst = sb + st * STAGE + j * CHB;
            if (it || !ex) bulk_g2s(dst + CH0, p.hk + (size_t)ch * S_, 4096, bhl + st * 8);
            if (one && j) break;
            bulk_g2s(dst + CU0, g_U + (size_t)ch * UCH, UARR, bfull + st * 8);
            bulk_g2s(dst + CU1, g_U + (size_t)ch * UCH + UARR, UARR, bfull + st * 8);
          }
          if (st >= 2 && !ex) tma2d(s_xt + (st - 2) * 16384, &m_x, bxt, c0 + (st - 2) * 64, tm * 128);
          if (st == 3) ph ^= 1;
        }
#pragma unroll 1
        for (int it = ex ? 28 + TL : 0; it < 28 + TL; it++) {
          int st = it & 3;
          uint32_t a = sb + st * STAGE, b = a + 16384;
          const int ix = it < 28 ? it : it - TL;
          const int k0 = (kh ^ (it >= 28)) * 1792 + (it < 16 ? (it >> 2) * 448 + st * 64 : (ix & 3) * 448 + (ix >> 2) * 64);
          if (it == W2P)
            asm volatile("cp.async.bulk.prefetch.tensor.5d.L2.global [%0, {%1, %3, %3, %3, %2}];" ::"l"(&m_w2), "r"(tn2 * 256 + ((rank ^ (2 * kh)) * 64)), "r"((mp * 448 + 384) >> 5), "r"(0) : "memory");
          if (it == 28) { mbar_wait(bdx, 0); fence_async(); }
          if (it == 0 || it == 16 || it == 20 || it == 24) { PSTAMP(64 + (it >> 1)); mbar_wait(bdep + (it ? (it - 8) * 2 : 8), 0); fence_async(); PSTAMP(65 + (it >> 1)); }
          mbar_wait(bempty + st * 8, ph);
          mbar_expect_tx(bfull + st * 8, it < NF ? STAGE : 32768);
          tma2d(a, &m_act, bfull + st * 8, k0, tm * 128);
#pragma unroll 1
          for (int j = it < NF ? rank * 2 : rank; j < (it < NF ? rank * 2 + 2 : rank + 1); j++) tma5d_mc(b + j * 8192, &m_w2, bfull + st * 8, tn2 * 256 + ((j ^ (2 * kh)) * 64), k0 >> 5);
          if (it == NF || it == NF + 1) mbar_arrive(it > NF ? bdep : bdep + 40);
          if (st == 3) ph ^= 1;
        }
      }
    } else if (warp == 1) {
      const unsigned par = ld_epoch() & 1;
#pragma unroll 1
      for (int t = ex ? 2 : 0; t < 2; t++) {
        const int l1 = 32 + (t ? lane & 15 : lane);
        uint2 bb = ldg64(p.b1 + jn * 448 + t * 256 + lane * 4), b2 = ldg64(p.b1 + jn * 448 + t * 256 + l1 * 4);
        bar_sync(NB_CS, 288);
        if (t == 0) PSTAMP(24);
#pragma unroll 1
        for (int h = 0, n = 0; h < 2; n++) {
          const int l = h ? l1 : lane;
          const float* src = g_csp + jn * 512 + t * 256 + l * 4;
          uint4 v[4];
          uint32_t bad = 0;
#pragma unroll
          for (int j = 0; j < 4; j++) v[j] = ldg128_rlx(src + j * 4096);
          float4 s = make_float4(0.f, 0.f, 0.f, 0.f);
#pragma unroll
          for (int j = 0; j < 4; j++) {
            bad |= (v[j].x ^ par) | (v[j].z ^ par);
            s.x += __uint_as_float(v[j].x); s.y += __uint_as_float(v[j].y); s.z += __uint_as_float(v[j].z); s.w += __uint_as_float(v[j].w);
          }
          if (!__any_sync(0xffffffff, bad & 1)) {
            const uint32_t dst = s_cb + (l >> 1) * 64 + (l & 1) * 8;
            const float r0 = s.x - rbf(s.x), r1 = s.y - rbf(s.y), r2 = s.z - rbf(s.z), r3 = s.w - rbf(s.w);
            sts64(dst, pack2(s.x, s.y), pack2(s.z, s.w));
            sts64(dst + 16, pack2(r0, r1), pack2(r2, r3));
            sts64(dst + 32, bb.x, bb.y);
            sts64(dst + 48, pack2(r0 - rbf(r0), r1 - rbf(r1)), pack2(r2 - rbf(r2), r3 - rbf(r3)));
            if (lane < 8) sts64(s_cb + 2048 + lane * 8, 0, 0);
            bb = b2;
            h++;
          }
          spin_guard(n);
        }
        if (EPM) asm volatile("fence.proxy.async.shared::cta;" ::: "memory");
        __syncwarp();
        if (lane <= t) mbar_arrive(bepi);
        PSTAMP(25 + t);
      }
#pragma unroll 1
      for (int i = ex; i < (ex ? 2 : 5); i++) {
        bar_sync(NB_ACT + i, 288);
        PSTAMP(80 + 2 * i);
        if (i == 1) {
          const int chb = chbase(), n0 = ex ? 32 : min(7, 128 - (chb & 127));
          if (lane == 0 || (lane == 1 && n0 < 7)) signal(C_Y + (chb >> 7) + lane, lane ? 7 - n0 : n0);
        } else if (lane == 0) signal(C_ACT + (tm * 2 + kh) * 4 + (i ? i - 1 : 0), 32);
        PSTAMP(81 + 2 * i);
        __syncwarp();
      }
    } else {
      const unsigned ep = ld_epoch();
      const int u_ = warp - 2;
      if (u_ == 0) {
        const bool up = (cta & 15) != 14 && !ex;
        if (lane == 0 && up) {
#pragma unroll 1
          for (int i = 2; i < 4; i++) {
            const uint32_t bb = bkv + (i & 1) * 8, buf = s_xt + (i & 1) * 16384;
            mbar_wait(i == 2 ? bkf : byf, 0);
            mbar_expect_tx(bb, 16384);
            tma3d(buf, &m_k, bb, (cta & 15) * 64, (cta >> 4) * 16 + i * 4);
            tma3d(buf + 8192, &m_v, bb, (cta & 15) * 64, (cta >> 4) * 16 + i * 4);
          }
        }
        __syncwarp();
        bar_sync(NB_U, 288);
        if (lane == 0) {
          PSTAMP(32);
          if (up || ex) signal(C_U + (ex ? 14 : cta & 15), ex ? 32 : 16);
          PSTAMP(30);
          wait_cnt(C_U + ((cta * 7) >> 6), ep);
          wait_cnt(C_U + ((cta * 7 + 6) >> 6), ep);
          mbar_arrive(bdep);
        }
      } else if (!ex) {
        bar_sync(NB_ST, 288);
        uint2 v[4];
#pragma unroll 1
        for (int n = 0;; n++) {
          uint32_t bad = 0;
#pragma unroll
          for (int j = 0; j < 4; j++) v[j] = ldg64_rlx(g_stat + tm * 128 + (lane >> 3) * 16 + (lane & 7) + (j >> 1) * 64 + (j & 1) * 8);
#pragma unroll
          for (int j = 0; j < 4; j++) bad |= v[j].y ^ ep;
          if (!__any_sync(0xffffffff, bad)) break;
          spin_guard(n);
        }
#pragma unroll
        for (int j = 0; j < 4; j += 2) sts64(s_st + lane * 8 + j * 128, v[j].x, v[j + 1].x);
        __syncwarp();
        if (lane == 0) mbar_arrive(bepi);
        PSTAMP(27);
      }
      __syncwarp();
      const int chb = chbase() + u_;
      const uint32_t dv = ldg16(p.Dv + chb + (lane & 15) * 2 + (lane & 8) * 6, 1);
#pragma unroll 1
      for (int it = 0; it < (ex ? 16 : 4); it++) {
        const int st = it & 3;
        const uint32_t hs = sb + st * STAGE + u_ * CHB;
        const uint4* hp_ = (const uint4*)(p.hk + (size_t)(chb + it * 2 + (it & 8) * 6) * S_) + lane;
        uint4 v[8];
#pragma unroll
        for (int j = 0; j < 8; j++) v[j] = ldg128(hp_ + j * 32);
        const uint32_t d0 = __shfl_sync(0xffffffff, dv, it), h0 = hadd2(v[0].x, lane ? 0x80008000u : d0 | 0x80000000u);
        uint32_t prev = 0;
#pragma unroll
        for (int j = 0; j < 8; j++) {
          const uint32_t r = __shfl_sync(0xffffffff, v[j].w, lane - 1), x = j ? v[j].x : h0;
          v[j] = make_uint4(__byte_perm(lane ? r : prev, x, 0x5432), __byte_perm(x, v[j].y, 0x5432), __byte_perm(v[j].y, v[j].z, 0x5432), __byte_perm(v[j].z, v[j].w, 0x5432));
          prev = r;
        }
        mbar_wait(bhl + st * 8, (it >> 2) & 1);
#pragma unroll
        for (int j = 0; j < 8; j++) sts128u(hs + CH1 + j * 512 + lane * 16, v[j].x, v[j].y, v[j].z, v[j].w);
        if (lane == 0) asm volatile("st.shared.b32 [%0], %1;" ::"r"(hs + CH0), "r"(h0) : "memory");
        __syncwarp();
        if (lane == 0) mbar_arrive(bh + st * 8);
        PSTAMP(52 + st);
      }
      if (lane == 0 && !ex) {
        if (u_ == 0) {
#pragma unroll 1
          for (int i = 0; i < 4; i++) { wait_cnt(C_ACT + (tm * 2 + kh) * 4 + i, ep); mbar_arrive(bdep + 8 + i * 8); }
          wait_cnt(C_ACT + (tm * 2 + (kh ^ 1)) * 4 + 3, ep);
          mbar_arrive(bdx);
        } else {
          wait_cnt(C_Y + (c0 >> 7), ep);
          asm volatile("red.relaxed.gpu.global.add.u32 [%0], 1;" ::"l"(g_cnt + C_TK * 32) : "memory");
          fence_async();
          mbar_wait(bxt, 0);
          mbar_expect_tx(bxt, 32768);
#pragma unroll 1
          for (int i = 0; i < 2; i++) {
            mbar_wait(i ? bdep : bdep + 40, i);
            tma2d(sb + ((NF + i) & 3) * STAGE + 32768, &m_y, bxt, tm * 128 + i * 64, c0);
          }
        }
      }
    }
  } else {
    asm volatile("setmaxnreg.inc.sync.aligned.u32 %0;" ::"n"(RC));
    const uint32_t e0 = mapa(bempty, 0), e1 = mapa(bempty, 1);
    uint32_t hp[48];
    asm volatile("barrier.cluster.wait.aligned;" ::: "memory");
    if (ex) {
      LOCALS;
      const int uch = 896 + (tid >> 2), uT = (cta & 3) * 512;
      const int rs_ = 4 * ((lane & 1) ^ 1) + 3 - ((lane >> 1) & 3);
      const uint32_t ma = ((lane >> 3) * 8 + rs_) * 128 + ((rs_ ^ (wg * 4 + w)) << 4);
      uint8_t* ub = g_U + (size_t)uch * UCH + (124 - (uT >> 4) + q) * 16;
      const bf16* kp = p.k + (size_t)uT * D_ + uch;
      const uint2 sw = ldg64(p.shk + uch * 4);
      uint32_t c0_ = ldg16(kp - 3 * D_, uT), c1_ = ldg16(kp - D_, uT) | (ldg16(kp - 2 * D_, uT) << 16);
      stg128(g_U + (size_t)(896 + (cta & 3) * 16) * UCH + (tid >> 3) * UARR + 2048 + (tid & 7) * 16, 0, 0, 0, 0);
#pragma unroll 1
      for (uint32_t i = 0; i < 8; i++) {
        ustep(true, sb + STAGE + i * 16384, ma, bdep + 8 + (i >> 1) * 8, 0, 0, false, ub - i * 64, sw, c0_, c1_, (lane & 28) | ((lane + 1) & 3), [&]() {});
        STAMP0(96 + i);
      }
      bar_arrive(NB_U, 288);
      if (WGU == 1) bar_arrive(NB_ORD0, 256);
#pragma unroll
      for (int i = 0; i < 48; i++) hp[i] = (PERT & 64) ? tid : 0;
    } else {
      uint32_t h0[64];
      {
        float d[128];
        LOCALS;
        G1COMMON(mma_n256, 4, SPL0, PRE0);
        const int uch = (cta & 15) * 64 + (wg * 4 + w) * 8 + g, uT = (cta >> 4) * 256;
        const int rs_ = 4 * ((lane & 1) ^ 1) + 3 - ((lane >> 1) & 3);
        unsigned ep = ld_epoch();
        const bf16* kp = p.k + (size_t)uT * D_ + uch;
        uint2 sw = ldg64(p.shk + uch * 4);
        uint32_t c0_ = ldg16(kp - 3 * D_, uT), c1_ = ldg16(kp - D_, uT) | (ldg16(kp - 2 * D_, uT) << 16);
        const int srow = tm * 128 + jn * 16 + (tid >> 4);
        const uint32_t xsb = sb + jn * 2048 + tid * 8;
        uint4 xv[8 - KS / 2];
        float pv = 0.f, s1[2] = {0.f, 0.f}, s2[2] = {0.f, 0.f};
        auto acc = [&](uint32_t e) {
          const float c0 = blo(e) - pv, c1 = bhi(e) - pv;
          s1[0] += c0; s1[1] += c1; s2[0] = fmaf(c0, c0, s2[0]); s2[1] = fmaf(c1, c1, s2[1]);
        };
        const bool umask = (cta & 15) != 14;
#pragma unroll 1
        for (uint32_t kb = 0; kb <= LG; kb++) {
          uint2 e;
          kstepx(kb, true, [&]() { e = lds64(xsb + (kb & 3) * STAGE); }, [&]() {
            if (kb == 0) { pv = __shfl_sync(0xffffffff, blo(e.x), lane & 16); STAMP(4 + wg); }
            acc(e.x); acc(e.y);
          });
          STAMP0(95 + kb);
          if (kb == 2) {
            asm volatile("" : "+r"(ep), "+r"(c0_), "+r"(c1_), "+r"(sw.x), "+r"(sw.y));
            asm volatile("st.shared.b32 [%0], %1;" ::"r"(s_par), "r"(ep & 1) : "memory");
            if (umask) *(uint2*)(g_U + (size_t)((cta & 15) * 64 + (cta >> 4) * 8) * UCH + (tid >> 4) * UARR + 2048 + (tid & 15) * 8) = make_uint2(0, 0);
          }
        }
        {
          const uint4* xp = (const uint4*)(p.x + (size_t)srow * D_ + ((KS + rot) & 15) * 64) + (tid & 15) + ((sw.x ^ sw.y ^ c0_ ^ c1_ ^ ep) & p.zero);
#pragma unroll
          for (int j = 0; j < 8 - KS / 2; j++) xv[j] = ldg128(xp + j * 16);
          if (LG == 7) cs_pub(ep & 1);
        }
        const uint32_t zr = p.zero, ma = cpx(((lane >> 3) * 8 + rs_) * 128 + ((rs_ ^ (wg * 4 + w)) << 4), zr), sl = cpx((lane & 28) | ((lane + 1) & 3), zr);
        uint8_t* ub = g_U + (size_t)uch * UCH + (124 - (uT >> 4) + q) * 16 + (7 - LG + UO) * 32;
#pragma unroll 1
        for (uint32_t kb = LG + 1; kb < 16; kb++) {
          const bool on = umask && (kb & 1) == UO && (LG == 7 || kb >= 8);
          const uint32_t i = (kb >> 1) & 3;
          if (PERT & 16) __syncwarp();
          auto step = [&]() {
            kstepx(kb, LG < 7 && kb < 8, [&]() {}, [&]() {
              if (LG < KS - 1 && kb < KS) {
                const uint2 e = lds64(xsb + (kb & 3) * STAGE);
                acc(e.x); acc(e.y);
              }
            });
          };
          if (UPOST) step();
          ustep(on, s_xt + (i & 1) * 16384, ma, bkv + (i & 1) * 8, i >> 1, i ? byf : bkf, lane == 0 && i < 2, ub, sw, c0_, c1_, sl, [&]() { if (!UPOST) step(); });
          ub -= 32;
          STAMP0(95 + kb);
          if (LG < 7 && kb == 7) cs_pub(ep & 1);
#pragma unroll
          for (int h = 0; h < 2; h++)
            if (kb == LG + LD + h * LD2) {
#pragma unroll
              for (int j = h * XH; j < (h ? 8 - KS / 2 : XH); j++) { asm volatile("" : "+r"(xv[j].x), "+r"(xv[j].y), "+r"(xv[j].z), "+r"(xv[j].w)); acc(xv[j].x); acc(xv[j].y); acc(xv[j].z); acc(xv[j].w); }
            }
          if (kb == (KS - 1 > LG + LD + LD2 ? KS - 1 : LG + LD + LD2)) {
            float m = s1[0] + s1[1], var = s2[0] + s2[1], sq;
#pragma unroll
            for (int o = 1; o < 16; o *= 2) { m += __shfl_xor_sync(0xffffffff, m, o); var += __shfl_xor_sync(0xffffffff, var, o); }
            m *= 1.f / D_;
            asm("sqrt.approx.ftz.f32 %0, %1;" : "=f"(sq) : "f"(rbf(rbf(fmaxf(fmaf(var, 1.f / D_, -m * m), 0.f)) + 1e-5f)));
            if (!(lane & 15)) stg128_rlx(g_stat + srow, pack2(sq, -(m + pv)), ep, 0, 0);
            bar_arrive(NB_ST, 288);
          }
        }
        bar_arrive(NB_U, 288);
        mbar_wait(bepi, 0);
        const uint2 st = g1_fix<32>(d, s_st, s_cb);
        wg_wait<EPW>();
        if (lane == 0) { mbar_arrive_remote(e0 + 24); mbar_arrive_remote(e1 + 24); }
        wg_wait<0>();
        STAMP(6 + wg);
        g1_epi<32>(d, h0, st);
        STAMP(8 + wg);
        if (PERT & 1) __syncwarp();
      }
      {
        float d[96];
        LOCALS;
        G1COMMON(mma_n192, 3, SPL1, PRE1);
        bf16* pa = g_act + (size_t)(tm * 128 + wg * 64 + w * 16 + g) * F_ + jn * 448 + q * 8;
        const uint2 sk = lds64(s_st + (wg * 32 + w * 8 + g) * 8);
        const float k0 = rcp(blo(sk.x)) * LOG2E, k1 = rcp(blo(sk.y)) * LOG2E;
        const float m1 = M1R ? __uint_as_float(cpx(0xbf800000u, tid & p.zero)) : -1.f;
#pragma unroll T1U
        for (uint32_t i = 0; i < 2; i++) {
#pragma unroll
          for (int s = 0; s < 8; s++) {
            if (s == PRK - 8 && i + wu == 2) bar_sync(NB_PRI, 256);
            kstepx(i * 8 + s, NOCS ? false : CSK || i == 0, [&]() {}, [&]() {
              if (s == 7 && i > wu) bar_arrive(NB_PRI, 256);
              act_chunk(h0 + 4 * s, pa + (s & 1) * 8 * F_ + (s >> 1) * 32, s & 1 ? k1 : k0, m1);
            });
            if (s < 2) STAMP0(90 + s + 2 * i);
          }
          if (BRK && i) break;
          if (i == 0) cs_pub(lds32(s_par));
#pragma unroll
          for (int s = 0; s < 32; s++) h0[s] = h0[s + 32];
          pa += 128;
        }
        bar_arrive(NB_ACT, 288);
        mbar_wait(bepi, 1);
        const uint2 st = g1_fix<24>(d, s_st, s_cb);
        if (EPO && wu == 1) bar_arrive(NB_ORD0, 256);
        wg_wait<EPW>();
        if (lane == 0) { mbar_arrive_remote(e0 + 24); mbar_arrive_remote(e1 + 24); }
        wg_wait<0>();
        if (!EPO && wu == 1) bar_arrive(NB_ORD0, 256);
        STAMP(10 + wg);
        g1_epi<24>(d, hp, st);
        STAMP(12 + wg);
        if (PERT & 2) __syncwarp();
      }
    }
    {
      LOCALS;
      float d[64];
      uint32_t xa[16], xb[16], xc[16], xd[16];
      const uint32_t hoff = ((g & 1) ? CH0 : CH1) + (64 * w + (g >> 1) + q - 7) * 4;
      const int wu = WGU;
      const uint32_t zr = p.zero, dbs0 = mkdesc(sb + CU0, CU1 - CU0) + wu * (CHB >> 4);
      const uint32_t xb_w = sb + (3 - wg) * STAGE + XOFF + lane * 8 + w * 3072;
      uint32_t xr_[3];
#pragma unroll
      for (int dw = 1; dw < 4; dw++) xr_[dw - 1] = xb_w + (w + dw > 3 ? -13056 : 0) + dw * 3072 + (2 + dw) * 256;
      auto xsts = [&](int c) {
#pragma unroll
        for (int i = 0; i < 3; i++)
          if (c || i >= w) sts64(xb_w + (c * 3 + i) * 256, pack2(d[16 * c + 4 * i], d[16 * c + 4 * i + 1 + HS]), pack2(d[16 * c + 4 * i + 2 - HS], d[16 * c + 4 * i + 3]));
      };
      uint32_t ub = sb + wg * CHB;
      if (PERT & 32) asm volatile("" : "+r"(ub));
      mbar_wait(bh, 0);
      mbar_wait(bfull, 0);
      loadA<0>(xa, ub + hoff); loadA<1>(xb, ub + hoff);
      const int chb = chbase(), last = ex ? 15 : 3 - wu;
#pragma unroll 1
      for (int it = 0; it <= last; it++) {
        const uint32_t hb = ub + hoff, dbs = dbs0 + (it & 3) * (STAGE >> 4);
        dupA(xa, zr);
        if (ORDF == 3 || PL) { loadA<2>(xc, hb); loadA<3>(xd, hb); }
        if (ORDF == 3) { dupA(xb, zr); xb[0] = cpx(xa[15], zr); dupA(xc, zr); dupA(xd, zr); xd[0] = cpx(xc[15], zr); }
        CSTAMP(0);
        if (HOFF == 9 && it) bar_sync(NB_WG0 + wu, 128);
        else bar_sync(NB_ORD0 + wu, 256);
        CSTAMP(1);
        if (ORDF != 3) { dupA(xb, zr); if (SHW) xb[0] = cpx(xa[15], zr); }
        mmaG<0>(d, xa, dbs);
        if (!PL) loadA<2>(xc, hb);
        mmaG<1>(d, xb, dbs); dupA(xc, zr);
        if (!PL) loadA<3>(xd, hb);
        wg_wait<1>(); loadA<4>(xa, hb); mmaG<2>(d, xc, dbs); dupA(xd, zr); if (SHW) xd[0] = cpx(xc[15], zr); dupA(xa, zr);
        if (HOFF == 4 && it + wu != (ex ? 16 : 3 + wu)) bar_arrive(NB_ORD0 + (wu ^ 1), 256);
        wg_wait<1>(); loadA<5>(xb, hb); mmaG<3>(d, xd, dbs); dupA(xb, zr); if (SHW) xb[0] = cpx(xa[15], zr); xsts(3);
        if (HOFF == 9 && it + wu == 0) bar_arrive(NB_ORD1, 256);
        if (HOFF == 3 && it + wu != (ex ? 16 : 3 + wu)) bar_arrive(NB_ORD0 + (wu ^ 1), 256);
        wg_wait<1>(); loadA<6>(xc, hb); mmaG<4>(d, xa, dbs); mmaG<5>(d, xb, dbs); dupA(xc, zr);
        if (HOFF == 5 && it + wu != (ex ? 16 : 3 + wu)) bar_arrive(NB_ORD0 + (wu ^ 1), 256);
        wg_wait<2>(); loadA<7>(xd, hb);
        if (HOFF == 0 && it + wu != (ex ? 16 : 3 + wu)) bar_arrive(NB_ORD0 + (wu ^ 1), 256);
        mmaG<6>(d, xc, dbs); dupA(xd, zr); if (SHW) xd[0] = cpx(xc[15], zr);
        if (HOFF == 1 && it + wu != (ex ? 16 : 3 + wu)) bar_arrive(NB_ORD0 + (wu ^ 1), 256);
        mmaG<7>(d, xd, dbs);
        if (HOFF == 2 && it + wu != (ex ? 16 : 3 + wu)) bar_arrive(NB_ORD0 + (wu ^ 1), 256);
        CSTAMP(2);
        xsts(2);
        if (PERT & 128) __syncwarp();
        bf16* yp = g_Y + (size_t)(chb + it * 2 + (it & 8) * 6 + wg) * S_ + 128 * w + 112 - 32 * (g >> 1) + 8 * (g & 1) + 2 * q;
        auto yout = [&](int a0, int a1) {
          uint2 t[12];
#pragma unroll
          for (int dw = 1; dw < 4; dw++) {
            if (a0 == 0) t[dw - 1] = lds64p<9 * 256>(xr_[dw - 1], w + dw > 3);
            if (a0 <= 1 && a1 > 1) t[dw + 2] = lds64p<6 * 256>(xr_[dw - 1], true);
            if (a0 <= 2 && a1 > 2) t[dw + 5] = lds64p<3 * 256>(xr_[dw - 1], true);
            if (a1 > 3) t[dw + 8] = lds64p<0>(xr_[dw - 1], true);
          }
#pragma unroll
          for (int a = a0; a < a1; a++) {
            const uint32_t s[2] = {hadd2(hadd2(t[3 * a].x, t[3 * a + 1].x), hadd2(t[3 * a + 2].x, pack2(d[60 - 16 * a], d[62 - 16 * a]))),
                                   hadd2(hadd2(t[3 * a].y, t[3 * a + 1].y), hadd2(t[3 * a + 2].y, pack2(d[61 - 16 * a], d[63 - 16 * a])))};
#pragma unroll
            for (int hh = 0; hh < 2; hh++)
              *(uint32_t*)(yp + 512 * a - 16 * hh) = movm(s[hh]);
          }
        };
        if (it < last) {
          const int sn = (it + 1) & 3;
          ub += sn ? STAGE : -3 * STAGE;
          mbar_wait(bh + sn * 8, ((it + 1) >> 2) & 1); mbar_wait(bfull + sn * 8, ((it + 1) >> 2) & 1);
        }
        wg_wait<2>();
        xsts(1);
        wg_wait<0>();
        CSTAMP(6);
        xsts(0);
        __syncwarp();
        if (lane == 0 && it < min(last, 12)) { mbar_arrive_remote(e0 + (it & 3) * 8); mbar_arrive_remote(e1 + (it & 3) * 8); }
        loadA<0>(xa, ub + hoff); loadA<1>(xb, ub + hoff);
        bar_sync(NB_WG0 + wu, 128);
        CSTAMP(3);
        yout(SHAD == 2 ? 3 : 0, 4);
      }
      bar_arrive(NB_Y, 288);
      asm volatile("" ::"r"(xa[0]), "r"(xb[15]) : "memory");
      __syncwarp();
      if (ex) { STAMP(14 + wg); return; }
      mbar_wait(bfull + 24, 0);
      if (lane == 0) {
        mbar_arrive_remote(e0 + 24); mbar_arrive_remote(e1 + 24);
        if (wg == 1) { mbar_arrive_remote(e0 + 16); mbar_arrive_remote(e1 + 16); }
      }
    }
    {
      LOCALS;
      STAMP(14 + wg);
      if (PERT & 4) __syncwarp();
      float d[128];
      const int wu = WGU;
      const uint32_t da0 = mkdesc(sb, 16) + wu * 512, db0 = mkdesc(sb + 16384, 8192);
      auto kstep = [&](uint32_t kb) {
        const uint32_t st = kb & 3, so = st * (STAGE >> 4);
        mbar_wait(bfull + st * 8, ((kb >> 2) & 1) ^ 1);
        wg_fence();
#pragma unroll
        for (int kk = 0; kk < 4; kk++) {
          mma_n256(d, da0 + (so + kk * 2), db0 + (so + kk * 128), kk || kb);
          if (kk == SPL2) {
            wg_commit();
            wg_wait<1>();
            if (kb && lane == 0) { mbar_arrive_remote(e0 + ((kb - 1) & 3) * 8); mbar_arrive_remote(e1 + ((kb - 1) & 3) * 8); }
            if (kk < 3) wg_fence();
          }
        }
        if (SPL2 < 3) wg_commit();
      };
      {
        bf16* pa = g_act + (size_t)(tm * 128 + wg * 64 + w * 16 + g) * F_ + jn * 448 + 256 + q * 8;
        const uint2 sk = lds64(s_st + (wg * 32 + w * 8 + g) * 8);
        const float k0 = rcp(blo(sk.x)) * LOG2E, k1 = rcp(blo(sk.y)) * LOG2E;
#pragma unroll 1
        for (uint32_t i = 0; i < 3; i++) {
#pragma unroll
          for (int s = 0; s < 4; s++) {
            kstep(i * 4 + s);
            act_chunk(hp + 4 * s, pa + (s & 1) * 8 * F_ + (s >> 1) * 32, s & 1 ? k1 : k0);
          }
          bar_arrive(NB_ACT + 2 + i, 288);
          if (BRK && i == 2) break;
#pragma unroll
          for (int s = 0; s < 32; s++) hp[s] = hp[s + 16];
          pa += 64;
          if (i) STAMP(38 + 2 * i + wg);
        }
      }
      mbar_wait(bxt, 0);
#pragma unroll 1
      for (uint32_t kb = 12; kb < NF; kb++) {
        kstep(kb);
        if (kb == 19) STAMP(44 + wg);
      }
      const int mr = lane & 7, mi = lane >> 3;
      uint32_t sr[32];
      const uint32_t xrow = s_xt + (wg * 64 + w * 16 + (mi & 1) * 8 + mr) * 128;
      const uint32_t yrow = sb + ((NF + wg) & 3) * STAGE + 32768 + ((mi >> 1) * 8 + mr) * 128 + (((w * 2 + (mi & 1)) ^ mr) << 4);
      const uint2 st = lds64(s_st + (wg * 32 + w * 8 + g) * 8);
      const uint32_t par = lds32(s_par);
      uint32_t pk[32];
      auto dopack = [&]() {
        STAMP(46 + wg);
        if (PERT & 8) __syncwarp();
        if (lane == 0) { mbar_arrive_remote(e0 + ((NF - 1) & 3) * 8); mbar_arrive_remote(e1 + ((NF - 1) & 3) * 8); }
#pragma unroll
        for (int i = 0; i < 32; i++) { pk[i] = pack2(d[64 + 2 * i], d[65 + 2 * i]); asm volatile("" : "+r"(pk[i])); }
      };
      if (!NODR) { wg_wait<0>(); dopack(); }
      uint4 r[8];
      const uint4* src = g_xch + (cta ^ PARTX) * 2048 + tid;
#pragma unroll
      for (int s = 0; s < 2 * TL; s++) {
        const uint32_t so = ((NF + s) & 3) * (STAGE >> 4);
        if (s == PT && wu == PTW && !RL0) bar_sync(NB_PRI, 256);
        if (RL0 ? (s == RLD && wu != PTW) || (s == PT && wu == PTW) : s == RLD) {
          STAMP(48 + wg);
          if (RL0 == 2 && s == PT) bar_sync(NB_PRI, 256);
#pragma unroll
          for (int j = 0; j < 8; j++) r[j] = ldg128_rlx(src + j * 256);
          if (RL0 == 1 && s == PT) bar_sync(NB_PRI, 256);
        }
        mbar_wait(bfull + ((NF + s) & 3) * 8, (((NF + s) >> 2) & 1) ^ 1);
        if (wg == 1) STAMP(111 + s);
        wg_fence();
#pragma unroll
        for (int kk = 0; kk < 4; kk++) {
          mma_n128(d, da0 + (so + kk * 2), db0 + (so + kk * 128), 1);
          if (kk == 0 && s >= 1 + PK2 && s <= 2 * TL - 4) {
            wg_commit();
            wg_wait<1>();
            if (lane == 0) { mbar_arrive_remote(e0 + ((NF + s - 1) & 3) * 8); mbar_arrive_remote(e1 + ((NF + s - 1) & 3) * 8); }
            wg_fence();
          }
        }
        wg_commit();
        if (PT < 2 * TL && s == 2 * TL - 1 && wu != PTW) bar_arrive(NB_PRI, 256);
        if (PK2 && s == 1) {
          uint4* dst = g_xch + cta * 2048 + tid;
          wg_wait<2>();
          STAMP(46 + wg);
#pragma unroll
          for (int h = 0; h < 2; h++) {
            if (h) wg_wait<1>();
            if (lane == 0) { mbar_arrive_remote(e0 + ((NF - 1 + h) & 3) * 8); mbar_arrive_remote(e1 + ((NF - 1 + h) & 3) * 8); }
#pragma unroll
            for (int j = h * PKH; j < (h ? 8 : PKH); j++)
              stg128_rlx(dst + j * 256, (pack2(d[64 + 8 * j], d[65 + 8 * j]) & ~1u) | par, pack2(d[66 + 8 * j], d[67 + 8 * j]), pack2(d[68 + 8 * j], d[69 + 8 * j]), pack2(d[70 + 8 * j], d[71 + 8 * j]));
          }
          STAMP(22 + wg);
        }
        if (!PK2 && s == 0 && NODR) { wg_wait<1>(); dopack(); }
        if (!PK2 && s >= XS && s < XS + 8 / XN) {
          uint4* dst = g_xch + cta * 2048 + tid;
#pragma unroll
          for (int j = (s - XS) * XN; j < (s - XS + 1) * XN; j++) stg128_rlx(dst + j * 256, (pk[4 * j] & ~1u) | par, pk[4 * j + 1], pk[4 * j + 2], pk[4 * j + 3]);
          STAMP(22 + wg);
        }
        if (s >= SRS && s < SRS + 8 / SRN) {
          if (s == SRS) mbar_wait(bxt, 1);
          const uint32_t nm[2] = {__byte_perm(st.x, 0, 0x3232), __byte_perm(st.y, 0, 0x3232)};
          const float rs[2] = {rcp(blo(st.x)), rcp(blo(st.y))};
#pragma unroll
          for (int jp = SRN * (s - SRS); jp < SRN * (s - SRS + 1); jp++) {
            uint32_t xr[4], xa = xrow + (jp >> 2) * 16384 + ((((jp & 3) * 2 + (mi >> 1)) ^ mr) << 4);
            ldsm4t(sr + 4 * jp, yrow + jp * 2048);
            asm volatile("ldmatrix.sync.aligned.m8n8.x4.shared.b16 {%0,%1,%2,%3}, [%4];" : "=r"(xr[0]), "=r"(xr[1]), "=r"(xr[2]), "=r"(xr[3]) : "r"(xa) : "memory");
#pragma unroll
            for (int m = 0; m < 4; m++) {
              uint32_t xc = hadd2(xr[m], nm[m & 1]);
              sr[4 * jp + m] = hmul2(pack2(blo(xc) * rs[m & 1], bhi(xc) * rs[m & 1]), sr[4 * jp + m]);
              asm volatile("" : "+r"(sr[4 * jp + m]));
            }
          }
        }
      }
      if (RLD == 2 * TL) {
#pragma unroll
        for (int j = 0; j < 8; j++) r[j] = ldg128_rlx(src + j * 256);
      }
      STAMP(16 + wg);
#pragma unroll 1
      for (int n = 0; n < SPINMAX; n++) {
        uint32_t bad = 0;
#pragma unroll
        for (int j = 0; j < 8; j++) bad |= r[j].x ^ par;
        if (!__any_sync(0xffffffff, bad & 1)) break;
#pragma unroll
        for (int j = 0; j < 8; j++) r[j] = ldg128_rlx(src + j * 256);
      }
      float rf[64];
#pragma unroll
      for (int j = 0; j < 8; j++) {
        const uint32_t e[4] = {r[j].x, r[j].y, r[j].z, r[j].w};
#pragma unroll
        for (int c = 0; c < 4; c++) {
          rf[8 * j + 2 * c] = blo(e[c]) * (SCL ? 1.f : -LOG2E); rf[8 * j + 2 * c + 1] = bhi(e[c]) * (SCL ? 1.f : -LOG2E);
          asm volatile("" : "+f"(rf[8 * j + 2 * c]), "+f"(rf[8 * j + 2 * c + 1]));
        }
      }
      STAMP(50 + wg);
      wg_wait<0>();
      STAMP(18 + wg);
#pragma unroll
      for (int jp = 0; jp < 8; jp++) {
        uint32_t o[4], xr[4], xa = xrow + (jp >> 2) * 16384 + ((((jp & 3) * 2 + (mi >> 1)) ^ mr) << 4);
        asm volatile("ldmatrix.sync.aligned.m8n8.x4.shared.b16 {%0,%1,%2,%3}, [%4];" : "=r"(xr[0]), "=r"(xr[1]), "=r"(xr[2]), "=r"(xr[3]) : "r"(xa) : "memory");
#pragma unroll
        for (int c = 0; c < 2; c++) {
          int j = jp * 2 + c;
          float z[4];
#pragma unroll
          for (int i = 0; i < 4; i++) z[i] = SCL ? d[4 * j + i] + rf[4 * j + i] : fmaf(d[4 * j + i], -LOG2E, rf[4 * j + i]);
          silu4(z);
#pragma unroll
          for (int hh = 0; hh < 2; hh++) {
            int m = c * 2 + hh;
            o[m] = hfma2(sr[4 * jp + m], pack2(z[2 * hh], z[2 * hh + 1]), xr[m]);
          }
        }
        asm volatile("stmatrix.sync.aligned.m8n8.x4.shared.b16 [%0], {%1,%2,%3,%4};" ::"r"(xa), "r"(o[0]), "r"(o[1]), "r"(o[2]), "r"(o[3]) : "memory");
        if (jp == 3 || jp == 7) {
          asm volatile("fence.proxy.async.shared::cta;" ::: "memory");
          __syncwarp();
          if (lane == 0) {
            tma2d_store(&m_out, s_xt + (jp >> 2) * 16384 + (wg * 64 + w * 16) * 128, c0 + (jp >> 2) * 64, tm * 128 + wg * 64 + w * 16);
            asm volatile("cp.async.bulk.commit_group;" ::: "memory");
          }
        }
      }
      if (lane == 0) asm volatile("cp.async.bulk.wait_group.read 0;" ::: "memory");
      STAMP(20 + wg);
    }
  }
}

typedef CUresult (*EncFn)(CUtensorMap*, CUtensorMapDataType, cuuint32_t, void*, const cuuint64_t*, const cuuint64_t*, const cuuint32_t*, const cuuint32_t*,
                          CUtensorMapInterleave, CUtensorMapSwizzle, CUtensorMapL2promotion, CUtensorMapFloatOOBfill);
static CUtensorMap mkmap(EncFn enc, const void* ptr, int rank, const uint64_t* dims, const uint64_t* strides, const uint32_t* box, CUtensorMapSwizzle sw) {
  CUtensorMap m;
  uint32_t es[5] = {1, 1, 1, 1, 1};
  enc(&m, CU_TENSOR_MAP_DATA_TYPE_BFLOAT16, rank, (void*)ptr, (const cuuint64_t*)dims, (const cuuint64_t*)strides, box, es, CU_TENSOR_MAP_INTERLEAVE_NONE, sw,
      CU_TENSOR_MAP_L2_PROMOTION_L2_256B, CU_TENSOR_MAP_FLOAT_OOB_FILL_NONE);
  return m;
}

extern "C" void kernel_launch(void* const* d_in, const int* in_sizes, int n_in, void* d_out, int out_size) {
  void* fn = nullptr;
  cudaDriverEntryPointQueryResult qr;
  cudaGetDriverEntryPoint("cuTensorMapEncodeTiled", &fn, cudaEnableDefault, &qr);
  EncFn enc = (EncFn)fn;
  void *act, *Y;
  cudaGetSymbolAddress(&act, g_act); cudaGetSymbolAddress(&Y, g_Y);
  uint64_t dx[2] = {D_, S_}, sx[1] = {D_ * 2};
  uint32_t b128[2] = {64, 128}, b16[2] = {64, 16};
  CUtensorMap m_x = mkmap(enc, d_in[0], 2, dx, sx, b128, CU_TENSOR_MAP_SWIZZLE_128B);
  CUtensorMap m_out = mkmap(enc, d_out, 2, dx, sx, b16, CU_TENSOR_MAP_SWIZZLE_128B);
  uint64_t dw1[3] = {64, D_, F_ / 64}, sw1[2] = {F_ * 2, 128};
  uint32_t bw1[3] = {64, 32, 4}, bw1b[3] = {64, 32, 3};
  CUtensorMap m_w1 = mkmap(enc, d_in[7], 3, dw1, sw1, bw1, CU_TENSOR_MAP_SWIZZLE_128B);
  CUtensorMap m_w1b = mkmap(enc, d_in[7], 3, dw1, sw1, bw1b, CU_TENSOR_MAP_SWIZZLE_128B);
  uint64_t da[2] = {F_, S_}, sa[1] = {F_ * 2};
  CUtensorMap m_act = mkmap(enc, act, 2, da, sa, b128, CU_TENSOR_MAP_SWIZZLE_128B);
  uint64_t dw2[5] = {D_, 2, 4, 4, F_ / 32}, sw2[4] = {D_ * 2, 8 * D_ * 2, 2 * D_ * 2, 32 * D_ * 2};
  uint32_t bw2[5] = {64, 2, 4, 4, 2};
  CUtensorMap m_w2 = mkmap(enc, d_in[9], 5, dw2, sw2, bw2, CU_TENSOR_MAP_SWIZZLE_128B);
  uint64_t dy[2] = {S_, D_}, sy[1] = {S_ * 2};
  CUtensorMap m_y = mkmap(enc, Y, 2, dy, sy, b128, CU_TENSOR_MAP_SWIZZLE_128B);
  uint64_t dk[3] = {D_, S_ / 16, 16}, sk[2] = {16 * D_ * 2, D_ * 2};
  uint32_t bkv[3] = {64, 4, 16};
  CUtensorMap m_k = mkmap(enc, d_in[1], 3, dk, sk, bkv, CU_TENSOR_MAP_SWIZZLE_128B);
  CUtensorMap m_v = mkmap(enc, d_in[2], 3, dk, sk, bkv, CU_TENSOR_MAP_SWIZZLE_128B);
  Params p;
  p.x = (const bf16*)d_in[0]; p.k = (const bf16*)d_in[1]; p.v = (const bf16*)d_in[2]; p.shk = (const bf16*)d_in[3];
  p.hk = (const bf16*)d_in[4]; p.Dv = (const bf16*)d_in[5]; p.b1 = (const bf16*)d_in[8]; p.w1 = (const bf16*)d_in[7]; p.zero = 0;
  cudaFuncSetAttribute(fused_kernel, cudaFuncAttributeMaxDynamicSharedMemorySize, SMEM_BYTES);
  fused_kernel<<<132, 384, SMEM_BYTES, cudaStreamPerThread>>>(m_x, m_w1, m_w1b, m_act, m_w2, m_y, m_out, m_k, m_v, p);
}
```
